```python
import torch

def _softmax(x, axis=-1):
    return torch.softmax(x, dim=axis)
def _gelu(x):
    return torch.nn.functional.gelu(x, approximate="tanh")
def _silu(x):
    return torch.nn.functional.silu(x)
def _sigmoid(x):
    return torch.sigmoid(x)
def _layernorm(x, axis=-1, eps=1e-5):
    m = x.mean(dim=axis, keepdim=True)
    v = x.var(dim=axis, keepdim=True, unbiased=False)
    return (x - m) / torch.sqrt(v + eps)
def _scatter_add(tgt, idx, src, axis=0):
    return tgt.clone().index_add_(axis, idx, src)
def _segment_sum(src, seg, n):
    out = torch.zeros((n,) + src.shape[1:], dtype=src.dtype)
    return out.index_add_(0, seg, src)
def _pad(x, pw):
    flat = tuple(v for pair in reversed(pw) for v in pair)
    return torch.nn.functional.pad(x, flat)

kernel_name = 'concat_heads__softmax_full_mha__spectral_fnet__prompt'

def setup_inputs():

    _w = (lambda a: (lambda t: t.to(torch.bfloat16) if t.is_floating_point() else t)(torch.as_tensor(a)))
    def _A_setup():
        B, S, D = 1, 2048, 640
        return {
            "x": _w((lambda *s: torch.randn(*s, dtype=torch.bfloat16) * 0.2)(B, S, D)),
            "wqkv": _w((lambda *s: torch.randn(*s, dtype=torch.bfloat16) * 0.8)(D, 3 * D)),
            "wo": _w((lambda *s: torch.randn(*s, dtype=torch.bfloat16) * 0.2)(D, D)),
        }
    _A_in = _A_setup()

    def _B_setup():
        B, S, D = 1, 2048, 640
        ns = torch.arange(S)[:, None] * torch.arange(S)[None, :]
        nd = torch.arange(D)[:, None] * torch.arange(D)[None, :]
        Ws_re = torch.cos(-2.0 * torch.pi * ns / S).to(float)
        Ws_im = torch.sin(-2.0 * torch.pi * ns / S).to(float)
        Wd_re = torch.cos(-2.0 * torch.pi * nd / D).to(float)
        Wd_im = torch.sin(-2.0 * torch.pi * nd / D).to(float)
        return {
            "x": _w((lambda *s: torch.randn(*s, dtype=torch.bfloat16) * 0.05)(B, S, D)),
            "dft_seq_re": _w(Ws_re),
            "dft_seq_im": _w(Ws_im),
            "dft_hid_re": _w(Wd_re),
            "dft_hid_im": _w(Wd_im),
        }
    _B_in = _B_setup()

    return {
        "A_x": _A_in["x"],
        "A_wqkv": _A_in["wqkv"],
        "A_wo": _A_in["wo"],
        "B_x": _B_in["x"],
        "B_dft_seq_re": _B_in["dft_seq_re"],
        "B_dft_seq_im": _B_in["dft_seq_im"],
        "B_dft_hid_re": _B_in["dft_hid_re"],
        "B_dft_hid_im": _B_in["dft_hid_im"],
    }

def reference(A_x, A_wqkv, A_wo, B_x, B_dft_seq_re, B_dft_seq_im, B_dft_hid_re, B_dft_hid_im):
    def _A_ref(x, wqkv, wo):
        B, S, D = x.shape
        H = 32; Dh = D // H
        qkv = (lambda x, *d: x.permute(*d))((x @ wqkv).reshape(B, S, 3, H, Dh), 2, 0, 3, 1, 4)
        q, k, v = qkv[0], qkv[1], qkv[2]
        scale = Dh ** -0.5
        scores = torch.einsum("bhqd,bhkd->bhqk", q, k) * scale
        p = _softmax(scores, axis=-1)
        o = torch.einsum("bhqk,bhkd->bhqd", p, v)
        return (lambda x, *d: x.permute(*d))(o, 0, 2, 1, 3).reshape(B, S, D) @ wo

    def _B_ref(x, dft_seq_re, dft_seq_im, dft_hid_re, dft_hid_im):
        a = torch.einsum("bsd,ed->bse", x, dft_hid_re)
        b = torch.einsum("bsd,ed->bse", x, dft_hid_im)
        y = torch.einsum("ts,bse->bte", dft_seq_re, a) - torch.einsum("ts,bse->bte", dft_seq_im, b)
        return y

    a = _A_ref(A_x, A_wqkv, A_wo)
    b = _B_ref(B_x, B_dft_seq_re, B_dft_seq_im, B_dft_hid_re, B_dft_hid_im)
    return torch.concatenate([a, b], axis=-1)
```

```cpp
#include <cuda_runtime.h>
#include <cuda_bf16.h>
#include <cuda.h>
#include <stdint.h>

namespace {

constexpr int SLOT = 53248;
constexpr int NSLOT = 4;
constexpr int BAR_OFF = SLOT * NSLOT;
constexpr int SMEM_BYTES = BAR_OFF + 128;
constexpr int LAG = 4;
constexpr uint32_t PMASK = 0xb5b5;
constexpr int O_GB = 16384, O_K = 26624, O_V = 32768, O_Q = 38912, O_KN = 45056;

__device__ __align__(1024) __nv_bfloat16 g_qkv[96 * 16 * 3072];
__device__ __align__(1024) __nv_bfloat16 g_ab[8 * 64 * 5120];
__device__ __align__(1024) __nv_bfloat16 g_o[16 * 80 * 1024];
__device__ __align__(1024) float g_kn[32 * 128];
__device__ unsigned g_cnt[32 * 32];
__device__ unsigned g_epoch[128];
#define STAMP(i) do {} while (0)

__device__ __forceinline__ void wgmma_rs_n128(float (&d)[64], uint32_t a0, uint32_t a1, uint32_t a2, uint32_t a3, uint64_t db, int scale_d) {
  asm volatile("{\n.reg .pred p;\nsetp.ne.b32 p, %69, 0;\n"
    "wgmma.mma_async.sync.aligned.m64n128k16.f32.bf16.bf16 {%0,%1,%2,%3,%4,%5,%6,%7,%8,%9,%10,%11,%12,%13,%14,%15,%16,%17,%18,%19,%20,%21,%22,%23,%24,%25,%26,%27,%28,%29,%30,%31,%32,%33,%34,%35,%36,%37,%38,%39,%40,%41,%42,%43,%44,%45,%46,%47,%48,%49,%50,%51,%52,%53,%54,%55,%56,%57,%58,%59,%60,%61,%62,%63}, {%64,%65,%66,%67}, %68, p, 1, 1, 0;\n}\n"
    : "+f"(d[0]), "+f"(d[1]), "+f"(d[2]), "+f"(d[3]), "+f"(d[4]), "+f"(d[5]), "+f"(d[6]), "+f"(d[7]), "+f"(d[8]), "+f"(d[9]),
      "+f"(d[10]), "+f"(d[11]), "+f"(d[12]), "+f"(d[13]), "+f"(d[14]), "+f"(d[15]), "+f"(d[16]), "+f"(d[17]), "+f"(d[18]), "+f"(d[19]),
      "+f"(d[20]), "+f"(d[21]), "+f"(d[22]), "+f"(d[23]), "+f"(d[24]), "+f"(d[25]), "+f"(d[26]), "+f"(d[27]), "+f"(d[28]), "+f"(d[29]),
      "+f"(d[30]), "+f"(d[31]), "+f"(d[32]), "+f"(d[33]), "+f"(d[34]), "+f"(d[35]), "+f"(d[36]), "+f"(d[37]), "+f"(d[38]), "+f"(d[39]),
      "+f"(d[40]), "+f"(d[41]), "+f"(d[42]), "+f"(d[43]), "+f"(d[44]), "+f"(d[45]), "+f"(d[46]), "+f"(d[47]), "+f"(d[48]), "+f"(d[49]),
      "+f"(d[50]), "+f"(d[51]), "+f"(d[52]), "+f"(d[53]), "+f"(d[54]), "+f"(d[55]), "+f"(d[56]), "+f"(d[57]), "+f"(d[58]), "+f"(d[59]),
      "+f"(d[60]), "+f"(d[61]), "+f"(d[62]), "+f"(d[63])
    : "r"(a0), "r"(a1), "r"(a2), "r"(a3), "l"(db), "r"(scale_d));
}
__device__ __forceinline__ void wgmma_rs_n128_init(float (&d)[64], uint32_t a0, uint32_t a1, uint32_t a2, uint32_t a3, uint64_t db) {
  asm volatile("{\n.reg .pred p;\nsetp.ne.b32 p, 0, 0;\n"
    "wgmma.mma_async.sync.aligned.m64n128k16.f32.bf16.bf16 {%0,%1,%2,%3,%4,%5,%6,%7,%8,%9,%10,%11,%12,%13,%14,%15,%16,%17,%18,%19,%20,%21,%22,%23,%24,%25,%26,%27,%28,%29,%30,%31,%32,%33,%34,%35,%36,%37,%38,%39,%40,%41,%42,%43,%44,%45,%46,%47,%48,%49,%50,%51,%52,%53,%54,%55,%56,%57,%58,%59,%60,%61,%62,%63}, {%64,%65,%66,%67}, %68, p, 1, 1, 0;\n}\n"
    : "=f"(d[0]), "=f"(d[1]), "=f"(d[2]), "=f"(d[3]), "=f"(d[4]), "=f"(d[5]), "=f"(d[6]), "=f"(d[7]), "=f"(d[8]), "=f"(d[9]),
      "=f"(d[10]), "=f"(d[11]), "=f"(d[12]), "=f"(d[13]), "=f"(d[14]), "=f"(d[15]), "=f"(d[16]), "=f"(d[17]), "=f"(d[18]), "=f"(d[19]),
      "=f"(d[20]), "=f"(d[21]), "=f"(d[22]), "=f"(d[23]), "=f"(d[24]), "=f"(d[25]), "=f"(d[26]), "=f"(d[27]), "=f"(d[28]), "=f"(d[29]),
      "=f"(d[30]), "=f"(d[31]), "=f"(d[32]), "=f"(d[33]), "=f"(d[34]), "=f"(d[35]), "=f"(d[36]), "=f"(d[37]), "=f"(d[38]), "=f"(d[39]),
      "=f"(d[40]), "=f"(d[41]), "=f"(d[42]), "=f"(d[43]), "=f"(d[44]), "=f"(d[45]), "=f"(d[46]), "=f"(d[47]), "=f"(d[48]), "=f"(d[49]),
      "=f"(d[50]), "=f"(d[51]), "=f"(d[52]), "=f"(d[53]), "=f"(d[54]), "=f"(d[55]), "=f"(d[56]), "=f"(d[57]), "=f"(d[58]), "=f"(d[59]),
      "=f"(d[60]), "=f"(d[61]), "=f"(d[62]), "=f"(d[63])
    : "r"(a0), "r"(a1), "r"(a2), "r"(a3), "l"(db));
}
__device__ __forceinline__ void wgmma_rs_n24_tb(float (&d)[12], uint32_t a0, uint32_t a1, uint32_t a2, uint32_t a3, uint64_t db, int scale_d) {
  asm volatile("{\n.reg .pred p;\nsetp.ne.b32 p, %17, 0;\n"
    "wgmma.mma_async.sync.aligned.m64n24k16.f32.bf16.bf16 {%0,%1,%2,%3,%4,%5,%6,%7,%8,%9,%10,%11}, {%12,%13,%14,%15}, %16, p, 1, 1, 1;\n}\n"
    : "+f"(d[0]), "+f"(d[1]), "+f"(d[2]), "+f"(d[3]), "+f"(d[4]), "+f"(d[5]), "+f"(d[6]), "+f"(d[7]), "+f"(d[8]), "+f"(d[9]),
      "+f"(d[10]), "+f"(d[11])
    : "r"(a0), "r"(a1), "r"(a2), "r"(a3), "l"(db), "r"(scale_d));
}
__device__ __forceinline__ void wgmma_ss_n160(float (&d)[80], uint64_t da, uint64_t db, int scale_d) {
  asm volatile("{\n.reg .pred p;\nsetp.ne.b32 p, %82, 0;\n"
    "wgmma.mma_async.sync.aligned.m64n160k16.f32.bf16.bf16 {%0,%1,%2,%3,%4,%5,%6,%7,%8,%9,%10,%11,%12,%13,%14,%15,%16,%17,%18,%19,%20,%21,%22,%23,%24,%25,%26,%27,%28,%29,%30,%31,%32,%33,%34,%35,%36,%37,%38,%39,%40,%41,%42,%43,%44,%45,%46,%47,%48,%49,%50,%51,%52,%53,%54,%55,%56,%57,%58,%59,%60,%61,%62,%63,%64,%65,%66,%67,%68,%69,%70,%71,%72,%73,%74,%75,%76,%77,%78,%79}, %80, %81, p, 1, 1, 0, 0;\n}\n"
    : "+f"(d[0]), "+f"(d[1]), "+f"(d[2]), "+f"(d[3]), "+f"(d[4]), "+f"(d[5]), "+f"(d[6]), "+f"(d[7]), "+f"(d[8]), "+f"(d[9]),
      "+f"(d[10]), "+f"(d[11]), "+f"(d[12]), "+f"(d[13]), "+f"(d[14]), "+f"(d[15]), "+f"(d[16]), "+f"(d[17]), "+f"(d[18]), "+f"(d[19]),
      "+f"(d[20]), "+f"(d[21]), "+f"(d[22]), "+f"(d[23]), "+f"(d[24]), "+f"(d[25]), "+f"(d[26]), "+f"(d[27]), "+f"(d[28]), "+f"(d[29]),
      "+f"(d[30]), "+f"(d[31]), "+f"(d[32]), "+f"(d[33]), "+f"(d[34]), "+f"(d[35]), "+f"(d[36]), "+f"(d[37]), "+f"(d[38]), "+f"(d[39]),
      "+f"(d[40]), "+f"(d[41]), "+f"(d[42]), "+f"(d[43]), "+f"(d[44]), "+f"(d[45]), "+f"(d[46]), "+f"(d[47]), "+f"(d[48]), "+f"(d[49]),
      "+f"(d[50]), "+f"(d[51]), "+f"(d[52]), "+f"(d[53]), "+f"(d[54]), "+f"(d[55]), "+f"(d[56]), "+f"(d[57]), "+f"(d[58]), "+f"(d[59]),
      "+f"(d[60]), "+f"(d[61]), "+f"(d[62]), "+f"(d[63]), "+f"(d[64]), "+f"(d[65]), "+f"(d[66]), "+f"(d[67]), "+f"(d[68]), "+f"(d[69]),
      "+f"(d[70]), "+f"(d[71]), "+f"(d[72]), "+f"(d[73]), "+f"(d[74]), "+f"(d[75]), "+f"(d[76]), "+f"(d[77]), "+f"(d[78]), "+f"(d[79])
    : "l"(da), "l"(db), "r"(scale_d));
}
__device__ __forceinline__ void wgmma_ss_n240_tb(float (&d)[120], uint64_t da, uint64_t db, int scale_d) {
  asm volatile("{\n.reg .pred p;\nsetp.ne.b32 p, %122, 0;\n"
    "wgmma.mma_async.sync.aligned.m64n240k16.f32.bf16.bf16 {%0,%1,%2,%3,%4,%5,%6,%7,%8,%9,%10,%11,%12,%13,%14,%15,%16,%17,%18,%19,%20,%21,%22,%23,%24,%25,%26,%27,%28,%29,%30,%31,%32,%33,%34,%35,%36,%37,%38,%39,%40,%41,%42,%43,%44,%45,%46,%47,%48,%49,%50,%51,%52,%53,%54,%55,%56,%57,%58,%59,%60,%61,%62,%63,%64,%65,%66,%67,%68,%69,%70,%71,%72,%73,%74,%75,%76,%77,%78,%79,%80,%81,%82,%83,%84,%85,%86,%87,%88,%89,%90,%91,%92,%93,%94,%95,%96,%97,%98,%99,%100,%101,%102,%103,%104,%105,%106,%107,%108,%109,%110,%111,%112,%113,%114,%115,%116,%117,%118,%119}, %120, %121, p, 1, 1, 0, 1;\n}\n"
    : "+f"(d[0]), "+f"(d[1]), "+f"(d[2]), "+f"(d[3]), "+f"(d[4]), "+f"(d[5]), "+f"(d[6]), "+f"(d[7]), "+f"(d[8]), "+f"(d[9]),
      "+f"(d[10]), "+f"(d[11]), "+f"(d[12]), "+f"(d[13]), "+f"(d[14]), "+f"(d[15]), "+f"(d[16]), "+f"(d[17]), "+f"(d[18]), "+f"(d[19]),
      "+f"(d[20]), "+f"(d[21]), "+f"(d[22]), "+f"(d[23]), "+f"(d[24]), "+f"(d[25]), "+f"(d[26]), "+f"(d[27]), "+f"(d[28]), "+f"(d[29]),
      "+f"(d[30]), "+f"(d[31]), "+f"(d[32]), "+f"(d[33]), "+f"(d[34]), "+f"(d[35]), "+f"(d[36]), "+f"(d[37]), "+f"(d[38]), "+f"(d[39]),
      "+f"(d[40]), "+f"(d[41]), "+f"(d[42]), "+f"(d[43]), "+f"(d[44]), "+f"(d[45]), "+f"(d[46]), "+f"(d[47]), "+f"(d[48]), "+f"(d[49]),
      "+f"(d[50]), "+f"(d[51]), "+f"(d[52]), "+f"(d[53]), "+f"(d[54]), "+f"(d[55]), "+f"(d[56]), "+f"(d[57]), "+f"(d[58]), "+f"(d[59]),
      "+f"(d[60]), "+f"(d[61]), "+f"(d[62]), "+f"(d[63]), "+f"(d[64]), "+f"(d[65]), "+f"(d[66]), "+f"(d[67]), "+f"(d[68]), "+f"(d[69]),
      "+f"(d[70]), "+f"(d[71]), "+f"(d[72]), "+f"(d[73]), "+f"(d[74]), "+f"(d[75]), "+f"(d[76]), "+f"(d[77]), "+f"(d[78]), "+f"(d[79]),
      "+f"(d[80]), "+f"(d[81]), "+f"(d[82]), "+f"(d[83]), "+f"(d[84]), "+f"(d[85]), "+f"(d[86]), "+f"(d[87]), "+f"(d[88]), "+f"(d[89]),
      "+f"(d[90]), "+f"(d[91]), "+f"(d[92]), "+f"(d[93]), "+f"(d[94]), "+f"(d[95]), "+f"(d[96]), "+f"(d[97]), "+f"(d[98]), "+f"(d[99]),
      "+f"(d[100]), "+f"(d[101]), "+f"(d[102]), "+f"(d[103]), "+f"(d[104]), "+f"(d[105]), "+f"(d[106]), "+f"(d[107]), "+f"(d[108]), "+f"(d[109]),
      "+f"(d[110]), "+f"(d[111]), "+f"(d[112]), "+f"(d[113]), "+f"(d[114]), "+f"(d[115]), "+f"(d[116]), "+f"(d[117]), "+f"(d[118]), "+f"(d[119])
    : "l"(da), "l"(db), "r"(scale_d));
}
__device__ __forceinline__ void wgmma_ss_n80_tb(float (&d)[40], uint64_t da, uint64_t db, int scale_d) {
  asm volatile("{\n.reg .pred p;\nsetp.ne.b32 p, %42, 0;\n"
    "wgmma.mma_async.sync.aligned.m64n80k16.f32.bf16.bf16 {%0,%1,%2,%3,%4,%5,%6,%7,%8,%9,%10,%11,%12,%13,%14,%15,%16,%17,%18,%19,%20,%21,%22,%23,%24,%25,%26,%27,%28,%29,%30,%31,%32,%33,%34,%35,%36,%37,%38,%39}, %40, %41, p, 1, 1, 0, 1;\n}\n"
    : "+f"(d[0]), "+f"(d[1]), "+f"(d[2]), "+f"(d[3]), "+f"(d[4]), "+f"(d[5]), "+f"(d[6]), "+f"(d[7]), "+f"(d[8]), "+f"(d[9]),
      "+f"(d[10]), "+f"(d[11]), "+f"(d[12]), "+f"(d[13]), "+f"(d[14]), "+f"(d[15]), "+f"(d[16]), "+f"(d[17]), "+f"(d[18]), "+f"(d[19]),
      "+f"(d[20]), "+f"(d[21]), "+f"(d[22]), "+f"(d[23]), "+f"(d[24]), "+f"(d[25]), "+f"(d[26]), "+f"(d[27]), "+f"(d[28]), "+f"(d[29]),
      "+f"(d[30]), "+f"(d[31]), "+f"(d[32]), "+f"(d[33]), "+f"(d[34]), "+f"(d[35]), "+f"(d[36]), "+f"(d[37]), "+f"(d[38]), "+f"(d[39])
    : "l"(da), "l"(db), "r"(scale_d));
}

__device__ __forceinline__ void wg_fence() { asm volatile("wgmma.fence.sync.aligned;" ::: "memory"); }
__device__ __forceinline__ void wg_commit() { asm volatile("wgmma.commit_group.sync.aligned;" ::: "memory"); }
template <int N> __device__ __forceinline__ void wg_wait() { asm volatile("wgmma.wait_group.sync.aligned %0;" ::"n"(N) : "memory"); }
__device__ __forceinline__ uint64_t mkdesc(uint32_t addr, uint32_t lbo, uint32_t sbo, uint32_t sw) {
    return (uint64_t)((addr & 0x3FFFF) >> 4) | ((uint64_t)(lbo >> 4) << 16) | ((uint64_t)(sbo >> 4) << 32) | ((uint64_t)sw << 62);
}
template <int N> __device__ __forceinline__ void pin(float (&r)[N]) {
#pragma unroll
    for (int i = 0; i < N; i++) asm volatile("" : "+f"(r[i])::"memory");
}
template <int N> __device__ __forceinline__ void pin(uint32_t (&r)[N]) {
#pragma unroll
    for (int i = 0; i < N; i++) asm volatile("" : "+r"(r[i])::"memory");
}
__device__ __forceinline__ uint32_t pack2(float lo, float hi) {
    uint32_t r;
    asm("cvt.rn.bf16x2.f32 %0, %1, %2;" : "=r"(r) : "f"(hi), "f"(lo));
    return r;
}
__device__ __forceinline__ void mbar_wait(uint32_t bar, uint32_t par) {
    asm volatile("{\n.reg .pred p;\n.reg .u32 c;\n"
                 "mbarrier.try_wait.parity.shared::cta.b64 p, [%0], %1;\n"
                 "@p bra DONE;\n"
                 "mov.u32 c, 0;\n"
                 "LOOP:\n"
                 "mbarrier.try_wait.parity.shared::cta.b64 p, [%0], %1;\n"
                 "@p bra DONE;\n"
                 "add.u32 c, c, 1;\n"
                 "setp.lt.u32 p, c, 4194304;\n"
                 "@p bra LOOP;\n"
                 "trap;\n"
                 "DONE:\n}" ::"r"(bar), "r"(par) : "memory");
}
__device__ __forceinline__ void mbar_expect(uint32_t bar, uint32_t bytes) {
    asm volatile("mbarrier.arrive.expect_tx.shared::cta.b64 _, [%0], %1;" ::"r"(bar), "r"(bytes) : "memory");
}
__device__ __forceinline__ void wait_cnt(const unsigned* c, unsigned target) {
    uint32_t tries = 0;
    while (true) {
        unsigned v;
        asm volatile("ld.acquire.gpu.global.u32 %0, [%1];" : "=r"(v) : "l"(c) : "memory");
        if ((int)(v - target) >= 0) break;
        if (++tries > (1u << 22)) __trap();
    }
}
__device__ __forceinline__ void proxy_fence() { asm volatile("fence.proxy.async.global;" ::: "memory"); }
__device__ __forceinline__ void publish(uint32_t bar, int lane) {
    __syncwarp();
    if (lane == 0) asm volatile("mbarrier.arrive.shared::cta.b64 _, [%0];" ::"r"(bar) : "memory");
}
__device__ __forceinline__ void tma2d(uint32_t dst, const CUtensorMap* tm, int c0, int c1, uint32_t bar) {
    asm volatile("cp.async.bulk.tensor.2d.shared::cluster.global.mbarrier::complete_tx::bytes [%0], [%1, {%3, %4}], [%2];"
                 ::"r"(dst), "l"(tm), "r"(bar), "r"(c0), "r"(c1) : "memory");
}
__device__ __forceinline__ void tma2d_mc(uint32_t dst, const CUtensorMap* tm, int c0, int c1, uint32_t bar) {
    asm volatile("cp.async.bulk.tensor.2d.shared::cluster.global.mbarrier::complete_tx::bytes.multicast::cluster [%0], [%1, {%3, %4}], [%2], %5;"
                 ::"r"(dst), "l"(tm), "r"(bar), "r"(c0), "r"(c1), "h"((uint16_t)3) : "memory");
}
__device__ __forceinline__ void tma3d(uint32_t dst, const CUtensorMap* tm, int c0, int c1, int c2, uint32_t bar) {
    asm volatile("cp.async.bulk.tensor.3d.shared::cluster.global.mbarrier::complete_tx::bytes [%0], [%1, {%3, %4, %5}], [%2];"
                 ::"r"(dst), "l"(tm), "r"(bar), "r"(c0), "r"(c1), "r"(c2) : "memory");
}
__device__ __forceinline__ void bulk(uint32_t dst, const void* src, uint32_t bytes, uint32_t bar) {
    asm volatile("cp.async.bulk.shared::cluster.global.mbarrier::complete_tx::bytes [%0], [%1], %2, [%3];"
                 ::"r"(dst), "l"(src), "r"(bytes), "r"(bar) : "memory");
}
__device__ __forceinline__ void bulk_mc(uint32_t dst, const void* src, uint32_t bytes, uint32_t bar) {
    asm volatile("cp.async.bulk.shared::cluster.global.mbarrier::complete_tx::bytes.multicast::cluster [%0], [%1], %2, [%3], %4;"
                 ::"r"(dst), "l"(src), "r"(bytes), "r"(bar), "h"((uint16_t)3) : "memory");
}
__device__ __forceinline__ void cluster_arrive() { asm volatile("barrier.cluster.arrive.release.aligned;" ::: "memory"); }
__device__ __forceinline__ void cluster_wait() { asm volatile("barrier.cluster.wait.acquire.aligned;" ::: "memory"); }
__device__ __forceinline__ void bsync(int id) { asm volatile("bar.sync %0, 256;" ::"r"(id) : "memory"); }
__device__ __forceinline__ void barrive(int id) { asm volatile("bar.arrive %0, 256;" ::"r"(id) : "memory"); }
__device__ __forceinline__ uint32_t lds32(uint32_t a) {
    uint32_t v;
    asm volatile("ld.shared.u32 %0, [%1];" : "=r"(v) : "r"(a) : "memory");
    return v;
}
__device__ __forceinline__ float bf_lo(uint32_t w) { return __uint_as_float(w << 16); }
__device__ __forceinline__ float bf_hi(uint32_t w) { return __uint_as_float(w & 0xffff0000u); }

__device__ __forceinline__ uint32_t exp_mufu(float a, float b) {
    float x, y;
    asm("ex2.approx.ftz.f32 %0, %1;" : "=f"(x) : "f"(a));
    asm("ex2.approx.ftz.f32 %0, %1;" : "=f"(y) : "f"(b));
    return pack2(x, y);
}
__device__ __forceinline__ uint32_t exp_poly(float a, float b) {
    uint32_t w, z, e, r, g;
    asm("prmt.b32 %0, %1, %2, 0x6521;" : "=r"(w) : "r"(__float_as_uint(a)), "r"(__float_as_uint(b)));
    asm("lop3.b32 %0, %1, 0x007f007f, 0x3f803f80, 0xEA;" : "=r"(z) : "r"(w));
    asm("lop3.b32 %0, %1, 0xff80ff80, 0x80008000, 0x6A;" : "=r"(e) : "r"(w));
    asm("fma.rn.bf16x2 %0, %1, %1, %2;" : "=r"(g) : "r"(z), "r"(0x40034003));
    asm("fma.rn.relu.bf16x2 %0, %1, %2, %3;" : "=r"(r) : "r"(e), "r"(g), "r"(0));
    return r;
}
__device__ __forceinline__ void exp_tile(float (&s)[64], uint32_t (&p)[32]) {
    pin(s);
#pragma unroll
    for (int b = 0; b < 16; b++) {
        if ((PMASK >> b) & 1) { p[2 * b] = exp_poly(s[4 * b], s[4 * b + 1]); p[2 * b + 1] = exp_poly(s[4 * b + 2], s[4 * b + 3]); }
        else { p[2 * b] = exp_mufu(s[4 * b], s[4 * b + 1]); p[2 * b + 1] = exp_mufu(s[4 * b + 2], s[4 * b + 3]); }
    }
    pin(p);
}

__device__ __forceinline__ void load24(float (&v)[24], const __nv_bfloat16* base, float sc, bool odd) {
#pragma unroll
    for (int pl = 0; pl < 3; pl++) {
        uint4 u = __ldcg(reinterpret_cast<const uint4*>(base + pl * 1024));
        if (pl == 2) { if (odd) { u.x = 0; u.y = 0; } else { u.z = 0; u.w = 0; } }
        v[8 * pl + 0] = bf_lo(u.x) * sc; v[8 * pl + 1] = bf_hi(u.x) * sc;
        v[8 * pl + 2] = bf_lo(u.y) * sc; v[8 * pl + 3] = bf_hi(u.y) * sc;
        v[8 * pl + 4] = bf_lo(u.z) * sc; v[8 * pl + 5] = bf_hi(u.z) * sc;
        v[8 * pl + 6] = bf_lo(u.w) * sc; v[8 * pl + 7] = bf_hi(u.w) * sc;
    }
}
__device__ __forceinline__ void attention_fallback(int h, int qm, int row0, int lane) {
    const bool odd = h & 1;
#pragma unroll 1
    for (int r = 0; r < 16; r++) {
        float q[24], acc[24];
        load24(q, g_qkv + (size_t)(h * 16 + qm) * 3072 + (row0 + r) * 8, 0x1p62f, odd);
#pragma unroll
        for (int i = 0; i < 24; i++) acc[i] = 0.f;
        float m = -INFINITY, l = 0.f;
#pragma unroll 1
        for (int j = lane; j < 2048; j += 32) {
            float kv[24];
            const int kr = j & 127;
            load24(kv, g_qkv + (size_t)((32 + h) * 16 + (j >> 7)) * 3072 + kr * 8, ((PMASK >> (kr >> 3)) & 1) ? 0x1p72f : 0x1p-62f, odd);
            float s = 0.f;
#pragma unroll
            for (int i = 0; i < 24; i++) s = fmaf(q[i], kv[i], s);
            const float mn = fmaxf(m, s);
            const float c = exp2f(m - mn), p = exp2f(s - mn);
            m = mn;
            l = l * c + p;
            load24(kv, g_qkv + (size_t)((64 + h) * 16 + (j >> 7)) * 3072 + kr * 8, 1.f, odd);
#pragma unroll
            for (int i = 0; i < 24; i++) acc[i] = fmaf(p, kv[i], acc[i] * c);
        }
        float M = m;
#pragma unroll
        for (int o = 16; o > 0; o >>= 1) M = fmaxf(M, __shfl_xor_sync(0xffffffffu, M, o));
        const float c = exp2f(m - M);
        l *= c;
#pragma unroll
        for (int o = 16; o > 0; o >>= 1) l += __shfl_xor_sync(0xffffffffu, l, o);
        float val = 0.f;
#pragma unroll
        for (int i = 0; i < 24; i++) {
            float a = acc[i] * c;
#pragma unroll
            for (int o = 16; o > 0; o >>= 1) a += __shfl_xor_sync(0xffffffffu, a, o);
            if (lane == i) val = a;
        }
        const bool valid = lane < 16 || (odd ? (lane >= 20 && lane < 24) : lane < 20);
        if (valid) {
            const int pl = lane >> 3;
            const int chunk = 5 * (h >> 1) + (pl == 2 ? 2 : pl + (odd ? 3 : 0));
            g_o[(size_t)(qm * 80 + chunk) * 1024 + (row0 + r) * 8 + (lane & 7)] = __float2bfloat16(val / l);
        }
    }
}

template <bool V> struct BoolC { static constexpr bool value = V; };
static_assert(LAG >= 2 && LAG % 2 == 0 && LAG <= 16, "");
struct Maps { CUtensorMap x, wqkv, bx, wr, wi, cr, ci, wo; };

__global__ void __cluster_dims__(2, 1, 1) __launch_bounds__(384, 1)
fused_kernel(const __grid_constant__ Maps tm, __nv_bfloat16* __restrict__ out) {
    extern __shared__ __align__(1024) uint8_t smem[];
    const uint32_t sb = (uint32_t)__cvta_generic_to_shared(smem);
    const uint32_t bar_full = sb + BAR_OFF, bar_empty = sb + BAR_OFF + 32, bar_pub = sb + BAR_OFF + 64;
    const int tid = threadIdx.x, lane = tid & 31;
    const int wg = __shfl_sync(0xffffffffu, tid >> 7, 0);
    const int b = blockIdx.x, pair = b >> 1, rank = b & 1;
    const int nt = pair & 7, mt = 2 * (pair >> 3) + rank;
    const int head = pair >> 1, quarter = 2 * (pair & 1) + rank;
    const int gi = pair >> 2, gj = 2 * (pair & 3) + rank;

    if (tid == 0) STAMP(0);
    if (tid == 256) {
#pragma unroll
        for (int i = 0; i < NSLOT; i++) {
            asm volatile("mbarrier.init.shared::cta.b64 [%0], 1;" ::"r"(bar_full + 8 * i));
            asm volatile("mbarrier.init.shared::cta.b64 [%0], 16;" ::"r"(bar_empty + 8 * i));
        }
#pragma unroll
        for (int i = 0; i < 6; i++) asm volatile("mbarrier.init.shared::cta.b64 [%0], 8;" ::"r"(bar_pub + 8 * i));
        asm volatile("fence.mbarrier_init.release.cluster;" ::: "memory");
    }
    __syncwarp();
    cluster_arrive();
    cluster_wait();

    if (wg == 2) {
        asm volatile("setmaxnreg.dec.sync.aligned.u32 40;");
        if (tid == 256) {
            const unsigned ep = g_epoch[b] + 1;
            uint32_t n = 0, sl, fb;
            auto acquire = [&](uint32_t bytes) {
                const uint32_t s = n & 3;
                sl = sb + s * SLOT;
                fb = bar_full + 8 * s;
                mbar_wait(bar_empty + 8 * s, ((n >> 2) & 1) ^ 1);
                mbar_expect(fb, bytes);
                n++;
            };
#pragma unroll 1
            for (int k = 0; k < 10; k++) {
                acquire(49152);
                tma2d(sl, &tm.x, 64 * k, 128 * mt, fb);
                tma2d_mc(sl + 16384 + rank * 16384, &tm.wqkv, 240 * nt + 128 * rank, 64 * k, fb);
                tma2d_mc(sl + 16384 + rank * 16384 + 8192, &tm.wqkv, 240 * nt + 128 * rank + 64, 64 * k, fb);
            }
#pragma unroll 1
            for (int k = 0; k < 10; k++) {
                acquire(16384 + 20480);
                tma2d(sl, &tm.bx, 64 * k, 128 * mt, fb);
                tma2d_mc(sl + 16384 + rank * 10240, rank ? &tm.wi : &tm.wr, 64 * k, 80 * nt, fb);
            }
            STAMP(16);
            wait_cnt(g_cnt + 32 * (head / 12), ep * 16);
            wait_cnt(g_cnt + 32 * ((32 + head) / 12), ep * 16);
            wait_cnt(g_cnt + 32 * ((64 + head) / 12), ep * 16);
            proxy_fence();
            STAMP(17);
            const __nv_bfloat16* kvsrc = g_qkv + (size_t)((32 + 32 * rank + head) * 16) * 3072;
#pragma unroll 1
            for (int it = 0; it < 64 + LAG; it++) {
                if (it == LAG) {
                    STAMP(18);
                    wait_cnt(g_cnt + 32 * (8 + gj), ep * 16);
                    proxy_fence();
                    STAMP(19);
                }
                const bool hasq = (it & 15) == 0 && it < 64;
                acquire((it < 64 ? 6144 : 0) + (it >= 1 && it <= 64 ? 6144 : 0) + (it >= LAG ? 26624 : 0) + (hasq ? 6144 : 0) + (it == 0 ? 512 : 0));
                const int kt = it - rank;
                if (kt >= 0 && kt < 64) bulk_mc(sl + O_K + rank * 6144, kvsrc + (kt & 15) * 3072, 6144, fb);
                if (hasq) bulk(sl + O_Q, g_qkv + (size_t)(head * 16 + quarter * 4 + (it >> 4)) * 3072, 6144, fb);
                if (it == 0) bulk(sl + O_KN, g_kn + head * 128, 512, fb);
                if (it >= LAG) {
                    const int g = it - LAG;
                    tma2d_mc(sl + rank * 8192, g < 32 ? &tm.cr : &tm.ci, 64 * (g & 31), 128 * gi + 64 * rank, fb);
                    bulk(sl + O_GB, g_ab + (size_t)(gj * 64 + g) * 5120, 10240, fb);
                }
            }
            const uint32_t n0 = n;
#pragma unroll 1
            for (int k = 0; k < 4; k++) {
                acquire(53248);
                tma3d(sl + 32768, &tm.wo, 0, 128 * k, 5 * gj, fb);
            }
            STAMP(20);
            wait_cnt(g_cnt + 32 * (16 + gi), ep * 32);
            proxy_fence();
            STAMP(21);
            const __nv_bfloat16* osrc = g_o + (size_t)(gi * 80 + 8 * rank) * 1024;
#pragma unroll 1
            for (int k = 0; k < 4; k++) {
                const uint32_t s = (n0 + k) & 3;
                bulk_mc(sb + s * SLOT + rank * 16384, osrc + k * 16384, 16384, bar_full + 8 * s);
            }
            acquire(53248);
            bulk_mc(sl + rank * 16384, osrc + 4 * 16384, 16384, fb);
            tma3d(sl + 32768, &tm.wo, 0, 512, 5 * gj, fb);
            g_epoch[b] = ep;
        } else if (tid == 288) {
#pragma unroll 1
            for (int e = 0; e < 6; e++) {
                mbar_wait(bar_pub + 8 * e, 0);
                proxy_fence();
                unsigned* c = g_cnt + 32 * (e == 0 ? nt : e == 1 ? 8 + nt : 16 + quarter * 4 + e - 2);
                asm volatile("red.release.gpu.global.add.u32 [%0], 1;" ::"l"(c) : "memory");
                STAMP(24 + e);
            }
        }
        __syncwarp();
        asm volatile("barrier.cluster.arrive.release.aligned;\nbarrier.cluster.wait.acquire.aligned;" ::: "memory");
    } else {
        asm volatile("setmaxnreg.inc.sync.aligned.u32 232;");
        const int warp = (tid >> 5) & 3, g8 = lane >> 2, tt = lane & 3;
        uint32_t rel_addr;
        asm("mapa.shared::cluster.u32 %0, %1, %2;" : "=r"(rel_addr) : "r"(bar_empty), "r"(lane & 1));
        auto release = [&](uint32_t n) {
            if (lane < 2) asm volatile("mbarrier.arrive.shared::cluster.b64 _, [%0];" ::"r"(rel_addr + 8 * (n & 3)) : "memory");
        };
        auto wait_full = [&](uint32_t n) { mbar_wait(bar_full + 8 * (n & 3), (n >> 2) & 1); __syncwarp(); };
        const int row0 = wg * 64 + warp * 16;

        {
            float acc[120];
#pragma unroll
            for (int i = 0; i < 120; i++) acc[i] = 0.f;
            pin(acc);
            const uint64_t da0 = mkdesc(sb + wg * 8192, 16, 1024, 1), db0 = mkdesc(sb + 16384, 8192, 1024, 1);
#pragma unroll 1
            for (uint32_t k = 0; k < 10; k++) {
                wait_full(k);
                if (tid == 0 && k == 0) STAMP(1);
                const uint64_t so = (k & 3) * (SLOT >> 4);
                wg_fence();
#pragma unroll
                for (int j = 0; j < 4; j++) wgmma_ss_n240_tb(acc, da0 + so + 2 * j, db0 + so + 128 * j, 1);
                wg_commit();
                wg_wait<1>();
                if (k > 0) release(k - 1);
            }
            wg_wait<0>();
            pin(acc);
            release(9);
            if (tid == 0) STAMP(2);
            const int blk = row0 >> 3;
            const bool pl0 = (PMASK >> blk) & 1, pl1 = (PMASK >> (blk + 1)) & 1, to = tt & 1;
            const float QS = 0.22360679774997896f * 1.4426950408889634f * 0x1p-62f;
            const uint32_t kaxp = to ? 0x172A1BB3u : 0x1FBE1B80u, kaxm = to ? 0u : 0x5E80u;
#pragma unroll
            for (int pp = 0; pp < 6; pp++) {
                const int slot = 12 * nt + 2 * pp, ty = slot >> 5;
                const float* a = &acc[20 * pp];
                const float sc0 = ty == 0 ? QS : ty == 1 ? (pl0 ? 0x1p-72f : 0x1p62f) : 1.f;
                const float sc1 = ty == 0 ? QS : ty == 1 ? (pl1 ? 0x1p-72f : 0x1p62f) : 1.f;
                const uint32_t axq = to ? 0x20802080u : 0x20800000u, axv = to ? 0u : 0x3F80u;
                const uint32_t ax0 = ty == 0 ? axq : ty == 1 ? (pl0 ? kaxp : kaxm) : axv;
                const uint32_t ax1 = ty == 0 ? axq : ty == 1 ? (pl1 ? kaxp : kaxm) : axv;
                uint32_t* dE = reinterpret_cast<uint32_t*>(g_qkv + (size_t)(slot * 16 + mt) * 3072) + (row0 + g8) * 4 + tt;
                uint32_t* dO = dE + 16 * 1536;
                const uint32_t w0 = pack2(a[8] * sc0, a[9] * sc0), w1 = pack2(a[10] * sc1, a[11] * sc1);
                dE[0] = pack2(a[0] * sc0, a[1] * sc0);        dE[32] = pack2(a[2] * sc1, a[3] * sc1);
                dE[512] = pack2(a[4] * sc0, a[5] * sc0);      dE[544] = pack2(a[6] * sc1, a[7] * sc1);
                dE[1024] = tt < 2 ? w0 : ax0;                 dE[1056] = tt < 2 ? w1 : ax1;
                dO[0] = pack2(a[12] * sc0, a[13] * sc0);      dO[32] = pack2(a[14] * sc1, a[15] * sc1);
                dO[512] = pack2(a[16] * sc0, a[17] * sc0);    dO[544] = pack2(a[18] * sc1, a[19] * sc1);
                dO[1024] = tt < 2 ? ax0 : w0;                 dO[1056] = tt < 2 ? ax1 : w1;
                if (ty == 1) {
                    const float m0 = a[8] * a[8] + a[9] * a[9], m1 = a[10] * a[10] + a[11] * a[11];
                    const float e0 = a[0] * a[0] + a[1] * a[1] + a[4] * a[4] + a[5] * a[5];
                    const float e1 = a[2] * a[2] + a[3] * a[3] + a[6] * a[6] + a[7] * a[7];
                    const float o0 = a[12] * a[12] + a[13] * a[13] + a[16] * a[16] + a[17] * a[17];
                    const float o1 = a[14] * a[14] + a[15] * a[15] + a[18] * a[18] + a[19] * a[19];
                    float k0 = (tt < 2 ? e0 : o0) + m0 + __shfl_xor_sync(0xffffffffu, tt < 2 ? o0 : e0, 2);
                    float k1 = (tt < 2 ? e1 : o1) + m1 + __shfl_xor_sync(0xffffffffu, tt < 2 ? o1 : e1, 2);
                    const float kk = (to ? k1 : k0) + __shfl_xor_sync(0xffffffffu, to ? k0 : k1, 1);
                    const uint32_t kb = __float_as_uint(kk) & 0x7fffffffu;
                    const uint32_t mE = __reduce_max_sync(0xffffffffu, tt < 2 ? kb : 0u);
                    const uint32_t mO = __reduce_max_sync(0xffffffffu, tt < 2 ? 0u : kb);
                    if (lane < 2) g_kn[(slot - 32 + lane) * 128 + mt * 8 + wg * 4 + warp] = __uint_as_float(lane ? mO : mE) * 1.02f;
                }
            }
            publish(bar_pub, lane);
            if (tid == 0) STAMP(3);
        }
        {
            float acc[80];
#pragma unroll
            for (int i = 0; i < 80; i++) acc[i] = 0.f;
            pin(acc);
            const uint64_t da0 = mkdesc(sb + wg * 8192, 16, 1024, 1), db0 = mkdesc(sb + 16384, 16, 1024, 1);
#pragma unroll 1
            for (uint32_t k = 10; k < 20; k++) {
                wait_full(k);
                const uint64_t so = (k & 3) * (SLOT >> 4);
                wg_fence();
#pragma unroll
                for (int j = 0; j < 4; j++) wgmma_ss_n160(acc, da0 + so + 2 * j, db0 + so + 2 * j, 1);
                wg_commit();
                wg_wait<1>();
                if (k > 10) release(k - 1);
            }
            wg_wait<0>();
            pin(acc);
            release(19);
            if (tid == 0) STAMP(4);
#pragma unroll
            for (int hb = 0; hb < 2; hb++) {
                const float sg = hb ? -1.f : 1.f;
                uint32_t* dst = reinterpret_cast<uint32_t*>(g_ab + (size_t)(nt * 64 + hb * 32 + 2 * mt + wg) * 5120) + (warp * 16 + g8) * 4;
#pragma unroll
                for (int r = 0; r < 2; r++) {
                    const float* a = &acc[40 * hb + 2 * r];
#pragma unroll
                    for (int q = 0; q < 2; q++) {
                        uint4 v;
                        v.x = pack2(a[16 * q + 0] * sg, a[16 * q + 1] * sg);
                        v.y = pack2(a[16 * q + 4] * sg, a[16 * q + 5] * sg);
                        v.z = pack2(a[16 * q + 8] * sg, a[16 * q + 9] * sg);
                        v.w = pack2(a[16 * q + 12] * sg, a[16 * q + 13] * sg);
                        *reinterpret_cast<uint4*>(dst + (4 * q + tt) * 256 + r * 32) = v;
                    }
                    dst[(8 + (tt & 1)) * 256 + r * 32 + (tt >> 1)] = pack2(a[32] * sg, a[33] * sg);
                    dst[(8 + (tt & 1)) * 256 + r * 32 + 2 + (tt >> 1)] = pack2(a[36] * sg, a[37] * sg);
                }
            }
            publish(bar_pub + 8, lane);
            if (tid == 0) STAMP(5);
        }
        uint32_t failmask = 0;
        {
            float s[64], o[12], d[40];
            uint32_t p0[32], p1[32], q[6];
#pragma unroll
            for (int i = 0; i < 12; i++) o[i] = 0.f;
#pragma unroll
            for (int i = 0; i < 40; i++) d[i] = 0.f;
#pragma unroll
            for (int i = 0; i < 32; i++) p1[i] = 0u;
            pin(o); pin(d); pin(p1);
            const bool odd = head & 1;
            const uint64_t dk0 = mkdesc(sb + O_K, 2048, 128, 0), dv0 = mkdesc(sb + O_V, 128, 2048, 0);
            const uint64_t da0 = mkdesc(sb + wg * 8192, 16, 1024, 1), db0 = mkdesc(sb + O_GB, 128, 1024, 0);
            float kmax2 = 0.f;
            bool badq = false, badq_prev = false;
            uint32_t zero = 0;
            asm volatile("" : "+r"(zero));

            auto o_epilogue = [&](int pass, bool bad) {
                const int src = (lane & ~3) | (odd ? 0 : 2);
                const float l0 = __shfl_sync(0xffffffffu, o[8], src), l1 = __shfl_sync(0xffffffffu, o[10], src);
                const bool dat = odd ? tt >= 2 : tt < 2;
                uint32_t x0 = 0, x1 = 0;
#pragma unroll
                for (int i = 0; i < 3; i++) {
                    if (i < 2 || dat) {
                        x0 = max(x0, max(__float_as_uint(o[4 * i]) & 0x7fffffffu, __float_as_uint(o[4 * i + 1]) & 0x7fffffffu));
                        x1 = max(x1, max(__float_as_uint(o[4 * i + 2]) & 0x7fffffffu, __float_as_uint(o[4 * i + 3]) & 0x7fffffffu));
                    }
                }
                x0 = max(x0, __shfl_xor_sync(0xffffffffu, x0, 1)); x1 = max(x1, __shfl_xor_sync(0xffffffffu, x1, 1));
                x0 = max(x0, __shfl_xor_sync(0xffffffffu, x0, 2)); x1 = max(x1, __shfl_xor_sync(0xffffffffu, x1, 2));
                const uint32_t TINY = (127 - 95) << 23;
                bad = bad || !(l0 >= 0x1p-95f && l0 <= 0x1p126f) || !(l1 >= 0x1p-95f && l1 <= 0x1p126f) ||
                      x0 >= 0x7f800000u || x1 >= 0x7f800000u || (l0 < 1.f && x0 < TINY) || (l1 < 1.f && x1 < TINY);
                if (__any_sync(0xffffffffu, bad)) {
                    failmask |= 1u << pass;
                } else {
                    const float i0 = 1.f / l0, i1 = 1.f / l1;
                    const int qm = quarter * 4 + pass;
                    uint32_t* dst = reinterpret_cast<uint32_t*>(g_o + (size_t)(qm * 80 + 5 * (head >> 1)) * 1024) + (row0 + g8) * 4 + tt;
                    uint32_t* d01 = dst + (odd ? 3 * 512 : 0);
                    d01[0] = pack2(o[0] * i0, o[1] * i0);     d01[32] = pack2(o[2] * i1, o[3] * i1);
                    d01[512] = pack2(o[4] * i0, o[5] * i0);   d01[544] = pack2(o[6] * i1, o[7] * i1);
                    if (dat) { dst[1024] = pack2(o[8] * i0, o[9] * i0); dst[1056] = pack2(o[10] * i1, o[11] * i1); }
                    publish(bar_pub + 16 + 8 * pass, lane);
                }
            };
            auto q_prep = [&](uint32_t slot_base, bool first) {
                if (first) {
                    const uint32_t a = slot_base + O_KN + lane * 16;
                    const uint32_t v = max(max(lds32(a), lds32(a + 4)), max(lds32(a + 8), lds32(a + 12)));
                    kmax2 = __uint_as_float(__reduce_max_sync(0xffffffffu, v));
                }
                const uint32_t a = slot_base + O_Q + (row0 + g8) * 16 + tt * 4;
                q[0] = lds32(a); q[1] = lds32(a + 128); q[2] = lds32(a + 2048); q[3] = lds32(a + 2048 + 128);
                q[4] = lds32(a + 4096); q[5] = lds32(a + 4096 + 128);
                const bool dat = odd ? tt >= 2 : tt < 2;
                float n0 = 0.f, n1 = 0.f;
#pragma unroll
                for (int i = 0; i < 3; i++) {
                    const float sc = (i < 2 || dat) ? 0x1p62f : 0.f;
                    float v;
                    v = bf_lo(q[2 * i]) * sc; n0 = fmaf(v, v, n0);
                    v = bf_hi(q[2 * i]) * sc; n0 = fmaf(v, v, n0);
                    v = bf_lo(q[2 * i + 1]) * sc; n1 = fmaf(v, v, n1);
                    v = bf_hi(q[2 * i + 1]) * sc; n1 = fmaf(v, v, n1);
                }
                n0 += __shfl_xor_sync(0xffffffffu, n0, 1); n1 += __shfl_xor_sync(0xffffffffu, n1, 1);
                n0 += __shfl_xor_sync(0xffffffffu, n0, 2); n1 += __shfl_xor_sync(0xffffffffu, n1, 2);
                const float B0 = sqrtf(n0 * kmax2), B1 = sqrtf(n1 * kmax2);
                const float m0 = fmaxf(0.5f * B0, B0 - 126.f), m1 = fmaxf(0.5f * B1, B1 - 126.f);
                badq = !(B0 + m0 <= 630.f) || !(B1 + m1 <= 630.f);
                const uint32_t mm = pack2(-m0 * 0x1p-62f, -m1 * 0x1p-62f);
                if (tt == (odd ? 0 : 2)) { q[4] = 0x20800000u | (mm & 0xffffu); q[5] = 0x20800000u | (mm >> 16); }
            };
            auto issue = [&](uint32_t it, uint32_t (&pi)[32], int pv_acc, auto with_g) {
                const uint64_t so = (it & 3) * (SLOT >> 4);
                bsync(1 + wg);
                wg_fence();
                wgmma_rs_n128_init(s, q[0], q[1], q[2], q[3], dk0 + so);
                wgmma_rs_n128(s, zero, zero, q[4], q[5], dk0 + so + 128, 1);
                wg_commit();
                wgmma_rs_n24_tb(o, pi[0], pi[1], pi[2], pi[3], dv0 + so, pv_acc);
#pragma unroll
                for (int k = 1; k < 8; k++) wgmma_rs_n24_tb(o, pi[4 * k], pi[4 * k + 1], pi[4 * k + 2], pi[4 * k + 3], dv0 + so + 16 * k, 1);
                if constexpr (decltype(with_g)::value) {
#pragma unroll
                    for (int j = 0; j < 4; j++) wgmma_ss_n80_tb(d, da0 + so + 2 * j, db0 + so + 16 * j, 1);
                }
                wg_commit();
                barrive(2 - wg);
            };
            auto two_tiles = [&](uint32_t it, auto with_g) {
                if ((it & 15) == 0) {
                    badq_prev = badq;
                    q_prep(sb + (it & 3) * SLOT, !decltype(with_g)::value);
                }
                pin(q);
                issue(it, p1, 1, with_g);
                wg_wait<1>();
                exp_tile(s, p0);
                wait_full(21 + it);
                wg_wait<0>();
                pin(o); pin(p1); pin(d);
                release(20 + it);
                if constexpr (decltype(with_g)::value) {
                    if ((it & 15) == 0) o_epilogue((it >> 4) - 1, badq_prev);
                    pin(o);
                }
                issue(it + 1, p0, (it & 15) != 0, with_g);
                wg_wait<1>();
                exp_tile(s, p1);
                wait_full(22 + it);
                wg_wait<0>();
                pin(o); pin(p0); pin(d);
                release(21 + it);
            };
            if (wg == 1) barrive(1);
            wait_full(20);
            if (tid == 0) STAMP(6);
#pragma unroll 1
            for (uint32_t it = 0; it < LAG; it += 2) two_tiles(it, BoolC<false>());
#pragma unroll 1
            for (uint32_t it = LAG; it < 64; it += 2) two_tiles(it, BoolC<true>());
            if (wg == 0) bsync(1);
            if (tid == 0) STAMP(7);
            {
                wg_fence();
#pragma unroll
                for (int k = 0; k < 8; k++) wgmma_rs_n24_tb(o, p1[4 * k], p1[4 * k + 1], p1[4 * k + 2], p1[4 * k + 3], dv0 + 16 * k, 1);
                wg_commit();
                wg_wait<0>();
                pin(o); pin(p1);
                wg_fence();
#pragma unroll
                for (int j = 0; j < 4; j++) wgmma_ss_n80_tb(d, da0 + 2 * j, db0 + 16 * j, 1);
                wg_commit();
                o_epilogue(3, badq);
                if (tid == 0) STAMP(8);
#pragma unroll 1
                for (uint32_t it = 65; it < 64 + LAG; it++) {
                    wait_full(20 + it);
                    const uint64_t so = (it & 3) * (SLOT >> 4);
                    wg_fence();
#pragma unroll
                    for (int j = 0; j < 4; j++) wgmma_ss_n80_tb(d, da0 + so + 2 * j, db0 + so + 16 * j, 1);
                    wg_commit();
                    wg_wait<1>();
                    release(20 + it - 1);
                }
                wg_wait<0>();
                pin(d);
                release(20 + 63 + LAG);
            }
            if (tid == 0) STAMP(9);
            {
                __nv_bfloat16* dst = out + (size_t)(128 * gi + row0 + g8) * 1280 + 640 + 80 * gj;
#pragma unroll
                for (int r = 0; r < 2; r++) {
                    const float* a = &d[2 * r];
#pragma unroll
                    for (int qq = 0; qq < 2; qq++) {
                        uint4 v;
                        v.x = pack2(a[16 * qq + 0], a[16 * qq + 1]);
                        v.y = pack2(a[16 * qq + 4], a[16 * qq + 5]);
                        v.z = pack2(a[16 * qq + 8], a[16 * qq + 9]);
                        v.w = pack2(a[16 * qq + 12], a[16 * qq + 13]);
                        *reinterpret_cast<uint4*>(dst + r * 8 * 1280 + 32 * qq + 8 * tt) = v;
                    }
                    uint2 u;
                    u.x = pack2(a[32], a[33]);
                    u.y = pack2(a[36], a[37]);
                    *reinterpret_cast<uint2*>(dst + r * 8 * 1280 + 64 + 4 * tt) = u;
                }
            }
        }
        if (failmask) {
#pragma unroll 1
            for (int pass = 0; pass < 4; pass++) {
                if ((failmask >> pass) & 1) {
                    attention_fallback(head, quarter * 4 + pass, row0, lane);
                    publish(bar_pub + 16 + 8 * pass, lane);
                }
            }
        }
        __syncwarp();
        if (tid == 0) STAMP(10);
        {
            float acc[40];
#pragma unroll
            for (int i = 0; i < 40; i++) acc[i] = 0.f;
            pin(acc);
            const uint64_t da0 = mkdesc(sb + wg * 1024, 2048, 128, 0), db0 = mkdesc(sb + 32768, 4096, 256, 3);
            constexpr uint32_t N0 = 20 + 64 + LAG;
#pragma unroll 1
            for (uint32_t k = N0; k < N0 + 5; k++) {
                wait_full(k);
                if (tid == 0 && k == N0) STAMP(11);
                const uint64_t so = (k & 3) * (SLOT >> 4);
                wg_fence();
#pragma unroll
                for (int j = 0; j < 8; j++) wgmma_ss_n80_tb(acc, da0 + so + 256 * j, db0 + so + 32 * j, 1);
                wg_commit();
                if (k == N0 + 1) { wg_wait<1>(); release(N0); }
            }
            wg_wait<0>();
            pin(acc);
            cluster_arrive();
            if (tid == 0) STAMP(12);
            const uint32_t stg = sb + ((N0 + 4) & 3) * SLOT + wg * 1024 + warp * 256;
#pragma unroll
            for (int j = 0; j < 10; j += 2) {
                const int c = j + (lane >> 4), r = lane & 15;
                const uint32_t a = stg + c * 2048 + ((r + c) & 15) * 16;
                asm volatile("stmatrix.sync.aligned.m8n8.x4.shared.b16 [%0], {%1, %2, %3, %4};" ::"r"(a),
                             "r"(pack2(acc[4 * j], acc[4 * j + 1])), "r"(pack2(acc[4 * j + 2], acc[4 * j + 3])),
                             "r"(pack2(acc[4 * j + 4], acc[4 * j + 5])), "r"(pack2(acc[4 * j + 6], acc[4 * j + 7])) : "memory");
            }
            __syncwarp();
            __nv_bfloat16* dst = out + (size_t)(128 * gi + row0) * 1280 + 80 * gj;
#pragma unroll
            for (int k = 0; k < 5; k++) {
                const int idx = lane + 32 * k, r = idx / 10, c = idx - 10 * r;
                uint4 v;
                asm volatile("ld.shared.v4.u32 {%0, %1, %2, %3}, [%4];" : "=r"(v.x), "=r"(v.y), "=r"(v.z), "=r"(v.w)
                             : "r"(stg + c * 2048 + ((r + c) & 15) * 16) : "memory");
                *reinterpret_cast<uint4*>(dst + r * 1280 + 8 * c) = v;
            }
            if (tid == 0) STAMP(13);
            cluster_wait();
        }
    }
}

typedef CUresult (*EncodeFn)(CUtensorMap*, CUtensorMapDataType, cuuint32_t, void*, const cuuint64_t*, const cuuint64_t*,
                             const cuuint32_t*, const cuuint32_t*, CUtensorMapInterleave, CUtensorMapSwizzle,
                             CUtensorMapL2promotion, CUtensorMapFloatOOBfill);

void make2d(EncodeFn enc, CUtensorMap* m, void* p, uint64_t cols, uint64_t rows, uint32_t bc, uint32_t br) {
    cuuint64_t dims[2] = {cols, rows}, strides[1] = {cols * 2};
    cuuint32_t box[2] = {bc, br}, es[2] = {1, 1};
    enc(m, CU_TENSOR_MAP_DATA_TYPE_BFLOAT16, 2, p, dims, strides, box, es, CU_TENSOR_MAP_INTERLEAVE_NONE,
        CU_TENSOR_MAP_SWIZZLE_128B, CU_TENSOR_MAP_L2_PROMOTION_L2_128B, CU_TENSOR_MAP_FLOAT_OOB_FILL_NONE);
}

}

extern "C" void kernel_launch(void* const* d_in, const int* in_sizes, int n_in, void* d_out, int out_size) {
    (void)in_sizes; (void)n_in; (void)out_size;
    void* fn = nullptr;
    cudaDriverEntryPointQueryResult qr;
    cudaGetDriverEntryPoint("cuTensorMapEncodeTiled", &fn, cudaEnableDefault, &qr);
    EncodeFn enc = (EncodeFn)fn;
    Maps m;
    make2d(enc, &m.x, d_in[0], 640, 2048, 64, 128);
    make2d(enc, &m.wqkv, d_in[1], 1920, 640, 64, 64);
    make2d(enc, &m.bx, d_in[3], 640, 2048, 64, 128);
    make2d(enc, &m.cr, d_in[4], 2048, 2048, 64, 64);
    make2d(enc, &m.ci, d_in[5], 2048, 2048, 64, 64);
    make2d(enc, &m.wr, d_in[6], 640, 640, 64, 80);
    make2d(enc, &m.wi, d_in[7], 640, 640, 64, 80);
    {
        cuuint64_t dims[3] = {16, 640, 40}, strides[2] = {1280, 32};
        cuuint32_t box[3] = {16, 128, 5}, es[3] = {1, 1, 1};
        enc(&m.wo, CU_TENSOR_MAP_DATA_TYPE_BFLOAT16, 3, d_in[2], dims, strides, box, es, CU_TENSOR_MAP_INTERLEAVE_NONE,
            CU_TENSOR_MAP_SWIZZLE_32B, CU_TENSOR_MAP_L2_PROMOTION_L2_128B, CU_TENSOR_MAP_FLOAT_OOB_FILL_NONE);
    }
    cudaFuncSetAttribute(fused_kernel, cudaFuncAttributeMaxDynamicSharedMemorySize, SMEM_BYTES);
    fused_kernel<<<128, 384, SMEM_BYTES>>>(m, (__nv_bfloat16*)d_out);
}
```

```cpp
#include <cuda_runtime.h>
#include <cuda_bf16.h>
#include <cuda.h>
#include <stdint.h>

namespace {

constexpr int SLOT = 53248;
constexpr int NSLOT = 4;
constexpr int X_OFF = SLOT * NSLOT;
constexpr int BAR_OFF = X_OFF + 18432;
constexpr int SMEM_BYTES = BAR_OFF + 512;
constexpr uint32_t SB = 1024;
constexpr int LAG = 8;
constexpr uint32_t PMASK = 0x1dfe;
constexpr int O_GB = 16384, O_K = 26624, O_V = 32768, O_Q = 38912, O_KN = 51200;
constexpr int O_W1 = 26624, O_W0 = 39424;
constexpr int B_FULL = 0, B_EMPTY = 32, B_PUB = 64, B_KVOK = 80, B_ABOK = 88, B_QLD = 96, B_QRDY = 112, B_OST = 144, B_KV2 = 176, B_GAOK = 184, B_LQD = 192, B_KNX = 200, B_W1 = 208,
              B_ST = 240, B_GO = 288, B_W0 = 296, B_OOK = 304, B_KN = 320, B_FAIL = 368, B_BADQ = 384, B_KN2 = 448;
__host__ __device__ constexpr int stage_off(int pp) { return pp < 2 ? X_OFF + pp * 12288 : (pp == 2 ? 0 : pp == 5 ? 1 : pp - 1) * SLOT + O_Q; }

__device__ __align__(1024) __nv_bfloat16 g_qkv[96 * 16 * 3072];
__device__ __align__(1024) __nv_bfloat16 g_ab[8 * 64 * 5120];
__device__ __align__(1024) __nv_bfloat16 g_o[16 * 80 * 1024];
__device__ __align__(1024) __nv_bfloat16 g_wo[8 * 8 * 6400];
__device__ __align__(1024) uint32_t g_kn[32 * 8];
__device__ unsigned g_cnt[36 * 32];
__device__ unsigned g_epoch[128];

__device__ __forceinline__ void wgmma_rs_n128(float (&d)[64], uint32_t a0, uint32_t a1, uint32_t a2, uint32_t a3, uint64_t db, int scale_d) {
  asm volatile("{\n.reg .pred p;\nsetp.ne.b32 p, %69, 0;\n"
    "wgmma.mma_async.sync.aligned.m64n128k16.f32.bf16.bf16 {%0,%1,%2,%3,%4,%5,%6,%7,%8,%9,%10,%11,%12,%13,%14,%15,%16,%17,%18,%19,%20,%21,%22,%23,%24,%25,%26,%27,%28,%29,%30,%31,%32,%33,%34,%35,%36,%37,%38,%39,%40,%41,%42,%43,%44,%45,%46,%47,%48,%49,%50,%51,%52,%53,%54,%55,%56,%57,%58,%59,%60,%61,%62,%63}, {%64,%65,%66,%67}, %68, p, 1, 1, 0;\n}\n"
    : "+f"(d[0]), "+f"(d[1]), "+f"(d[2]), "+f"(d[3]), "+f"(d[4]), "+f"(d[5]), "+f"(d[6]), "+f"(d[7]), "+f"(d[8]), "+f"(d[9]),
      "+f"(d[10]), "+f"(d[11]), "+f"(d[12]), "+f"(d[13]), "+f"(d[14]), "+f"(d[15]), "+f"(d[16]), "+f"(d[17]), "+f"(d[18]), "+f"(d[19]),
      "+f"(d[20]), "+f"(d[21]), "+f"(d[22]), "+f"(d[23]), "+f"(d[24]), "+f"(d[25]), "+f"(d[26]), "+f"(d[27]), "+f"(d[28]), "+f"(d[29]),
      "+f"(d[30]), "+f"(d[31]), "+f"(d[32]), "+f"(d[33]), "+f"(d[34]), "+f"(d[35]), "+f"(d[36]), "+f"(d[37]), "+f"(d[38]), "+f"(d[39]),
      "+f"(d[40]), "+f"(d[41]), "+f"(d[42]), "+f"(d[43]), "+f"(d[44]), "+f"(d[45]), "+f"(d[46]), "+f"(d[47]), "+f"(d[48]), "+f"(d[49]),
      "+f"(d[50]), "+f"(d[51]), "+f"(d[52]), "+f"(d[53]), "+f"(d[54]), "+f"(d[55]), "+f"(d[56]), "+f"(d[57]), "+f"(d[58]), "+f"(d[59]),
      "+f"(d[60]), "+f"(d[61]), "+f"(d[62]), "+f"(d[63])
    : "r"(a0), "r"(a1), "r"(a2), "r"(a3), "l"(db), "r"(scale_d));
}
__device__ __forceinline__ void wgmma_rs_n128_init(float (&d)[64], uint32_t a0, uint32_t a1, uint32_t a2, uint32_t a3, uint64_t db) {
  asm volatile("{\n.reg .pred p;\nsetp.ne.b32 p, 0, 0;\n"
    "wgmma.mma_async.sync.aligned.m64n128k16.f32.bf16.bf16 {%0,%1,%2,%3,%4,%5,%6,%7,%8,%9,%10,%11,%12,%13,%14,%15,%16,%17,%18,%19,%20,%21,%22,%23,%24,%25,%26,%27,%28,%29,%30,%31,%32,%33,%34,%35,%36,%37,%38,%39,%40,%41,%42,%43,%44,%45,%46,%47,%48,%49,%50,%51,%52,%53,%54,%55,%56,%57,%58,%59,%60,%61,%62,%63}, {%64,%65,%66,%67}, %68, p, 1, 1, 0;\n}\n"
    : "=f"(d[0]), "=f"(d[1]), "=f"(d[2]), "=f"(d[3]), "=f"(d[4]), "=f"(d[5]), "=f"(d[6]), "=f"(d[7]), "=f"(d[8]), "=f"(d[9]),
      "=f"(d[10]), "=f"(d[11]), "=f"(d[12]), "=f"(d[13]), "=f"(d[14]), "=f"(d[15]), "=f"(d[16]), "=f"(d[17]), "=f"(d[18]), "=f"(d[19]),
      "=f"(d[20]), "=f"(d[21]), "=f"(d[22]), "=f"(d[23]), "=f"(d[24]), "=f"(d[25]), "=f"(d[26]), "=f"(d[27]), "=f"(d[28]), "=f"(d[29]),
      "=f"(d[30]), "=f"(d[31]), "=f"(d[32]), "=f"(d[33]), "=f"(d[34]), "=f"(d[35]), "=f"(d[36]), "=f"(d[37]), "=f"(d[38]), "=f"(d[39]),
      "=f"(d[40]), "=f"(d[41]), "=f"(d[42]), "=f"(d[43]), "=f"(d[44]), "=f"(d[45]), "=f"(d[46]), "=f"(d[47]), "=f"(d[48]), "=f"(d[49]),
      "=f"(d[50]), "=f"(d[51]), "=f"(d[52]), "=f"(d[53]), "=f"(d[54]), "=f"(d[55]), "=f"(d[56]), "=f"(d[57]), "=f"(d[58]), "=f"(d[59]),
      "=f"(d[60]), "=f"(d[61]), "=f"(d[62]), "=f"(d[63])
    : "r"(a0), "r"(a1), "r"(a2), "r"(a3), "l"(db));
}
__device__ __forceinline__ void wgmma_rs_n24_tb(float (&d)[12], uint32_t a0, uint32_t a1, uint32_t a2, uint32_t a3, uint64_t db, int scale_d) {
  asm volatile("{\n.reg .pred p;\nsetp.ne.b32 p, %17, 0;\n"
    "wgmma.mma_async.sync.aligned.m64n24k16.f32.bf16.bf16 {%0,%1,%2,%3,%4,%5,%6,%7,%8,%9,%10,%11}, {%12,%13,%14,%15}, %16, p, 1, 1, 1;\n}\n"
    : "+f"(d[0]), "+f"(d[1]), "+f"(d[2]), "+f"(d[3]), "+f"(d[4]), "+f"(d[5]), "+f"(d[6]), "+f"(d[7]), "+f"(d[8]), "+f"(d[9]),
      "+f"(d[10]), "+f"(d[11])
    : "r"(a0), "r"(a1), "r"(a2), "r"(a3), "l"(db), "r"(scale_d));
}
__device__ __forceinline__ void wgmma_ss_n160(float (&d)[80], uint64_t da, uint64_t db, int scale_d) {
  asm volatile("{\n.reg .pred p;\nsetp.ne.b32 p, %82, 0;\n"
    "wgmma.mma_async.sync.aligned.m64n160k16.f32.bf16.bf16 {%0,%1,%2,%3,%4,%5,%6,%7,%8,%9,%10,%11,%12,%13,%14,%15,%16,%17,%18,%19,%20,%21,%22,%23,%24,%25,%26,%27,%28,%29,%30,%31,%32,%33,%34,%35,%36,%37,%38,%39,%40,%41,%42,%43,%44,%45,%46,%47,%48,%49,%50,%51,%52,%53,%54,%55,%56,%57,%58,%59,%60,%61,%62,%63,%64,%65,%66,%67,%68,%69,%70,%71,%72,%73,%74,%75,%76,%77,%78,%79}, %80, %81, p, 1, 1, 0, 0;\n}\n"
    : "+f"(d[0]), "+f"(d[1]), "+f"(d[2]), "+f"(d[3]), "+f"(d[4]), "+f"(d[5]), "+f"(d[6]), "+f"(d[7]), "+f"(d[8]), "+f"(d[9]),
      "+f"(d[10]), "+f"(d[11]), "+f"(d[12]), "+f"(d[13]), "+f"(d[14]), "+f"(d[15]), "+f"(d[16]), "+f"(d[17]), "+f"(d[18]), "+f"(d[19]),
      "+f"(d[20]), "+f"(d[21]), "+f"(d[22]), "+f"(d[23]), "+f"(d[24]), "+f"(d[25]), "+f"(d[26]), "+f"(d[27]), "+f"(d[28]), "+f"(d[29]),
      "+f"(d[30]), "+f"(d[31]), "+f"(d[32]), "+f"(d[33]), "+f"(d[34]), "+f"(d[35]), "+f"(d[36]), "+f"(d[37]), "+f"(d[38]), "+f"(d[39]),
      "+f"(d[40]), "+f"(d[41]), "+f"(d[42]), "+f"(d[43]), "+f"(d[44]), "+f"(d[45]), "+f"(d[46]), "+f"(d[47]), "+f"(d[48]), "+f"(d[49]),
      "+f"(d[50]), "+f"(d[51]), "+f"(d[52]), "+f"(d[53]), "+f"(d[54]), "+f"(d[55]), "+f"(d[56]), "+f"(d[57]), "+f"(d[58]), "+f"(d[59]),
      "+f"(d[60]), "+f"(d[61]), "+f"(d[62]), "+f"(d[63]), "+f"(d[64]), "+f"(d[65]), "+f"(d[66]), "+f"(d[67]), "+f"(d[68]), "+f"(d[69]),
      "+f"(d[70]), "+f"(d[71]), "+f"(d[72]), "+f"(d[73]), "+f"(d[74]), "+f"(d[75]), "+f"(d[76]), "+f"(d[77]), "+f"(d[78]), "+f"(d[79])
    : "l"(da), "l"(db), "r"(scale_d));
}
__device__ __forceinline__ void wgmma_ss_n160_init(float (&d)[80], uint64_t da, uint64_t db) {
  asm volatile("{\n.reg .pred p;\nsetp.ne.b32 p, 0, 0;\n"
    "wgmma.mma_async.sync.aligned.m64n160k16.f32.bf16.bf16 {%0,%1,%2,%3,%4,%5,%6,%7,%8,%9,%10,%11,%12,%13,%14,%15,%16,%17,%18,%19,%20,%21,%22,%23,%24,%25,%26,%27,%28,%29,%30,%31,%32,%33,%34,%35,%36,%37,%38,%39,%40,%41,%42,%43,%44,%45,%46,%47,%48,%49,%50,%51,%52,%53,%54,%55,%56,%57,%58,%59,%60,%61,%62,%63,%64,%65,%66,%67,%68,%69,%70,%71,%72,%73,%74,%75,%76,%77,%78,%79}, %80, %81, p, 1, 1, 0, 0;\n}\n"
    : "=f"(d[0]), "=f"(d[1]), "=f"(d[2]), "=f"(d[3]), "=f"(d[4]), "=f"(d[5]), "=f"(d[6]), "=f"(d[7]), "=f"(d[8]), "=f"(d[9]),
      "=f"(d[10]), "=f"(d[11]), "=f"(d[12]), "=f"(d[13]), "=f"(d[14]), "=f"(d[15]), "=f"(d[16]), "=f"(d[17]), "=f"(d[18]), "=f"(d[19]),
      "=f"(d[20]), "=f"(d[21]), "=f"(d[22]), "=f"(d[23]), "=f"(d[24]), "=f"(d[25]), "=f"(d[26]), "=f"(d[27]), "=f"(d[28]), "=f"(d[29]),
      "=f"(d[30]), "=f"(d[31]), "=f"(d[32]), "=f"(d[33]), "=f"(d[34]), "=f"(d[35]), "=f"(d[36]), "=f"(d[37]), "=f"(d[38]), "=f"(d[39]),
      "=f"(d[40]), "=f"(d[41]), "=f"(d[42]), "=f"(d[43]), "=f"(d[44]), "=f"(d[45]), "=f"(d[46]), "=f"(d[47]), "=f"(d[48]), "=f"(d[49]),
      "=f"(d[50]), "=f"(d[51]), "=f"(d[52]), "=f"(d[53]), "=f"(d[54]), "=f"(d[55]), "=f"(d[56]), "=f"(d[57]), "=f"(d[58]), "=f"(d[59]),
      "=f"(d[60]), "=f"(d[61]), "=f"(d[62]), "=f"(d[63]), "=f"(d[64]), "=f"(d[65]), "=f"(d[66]), "=f"(d[67]), "=f"(d[68]), "=f"(d[69]),
      "=f"(d[70]), "=f"(d[71]), "=f"(d[72]), "=f"(d[73]), "=f"(d[74]), "=f"(d[75]), "=f"(d[76]), "=f"(d[77]), "=f"(d[78]), "=f"(d[79])
    : "l"(da), "l"(db));
}
__device__ __forceinline__ void wgmma_ss_n240_tb(float (&d)[120], uint64_t da, uint64_t db, int scale_d) {
  asm volatile("{\n.reg .pred p;\nsetp.ne.b32 p, %122, 0;\n"
    "wgmma.mma_async.sync.aligned.m64n240k16.f32.bf16.bf16 {%0,%1,%2,%3,%4,%5,%6,%7,%8,%9,%10,%11,%12,%13,%14,%15,%16,%17,%18,%19,%20,%21,%22,%23,%24,%25,%26,%27,%28,%29,%30,%31,%32,%33,%34,%35,%36,%37,%38,%39,%40,%41,%42,%43,%44,%45,%46,%47,%48,%49,%50,%51,%52,%53,%54,%55,%56,%57,%58,%59,%60,%61,%62,%63,%64,%65,%66,%67,%68,%69,%70,%71,%72,%73,%74,%75,%76,%77,%78,%79,%80,%81,%82,%83,%84,%85,%86,%87,%88,%89,%90,%91,%92,%93,%94,%95,%96,%97,%98,%99,%100,%101,%102,%103,%104,%105,%106,%107,%108,%109,%110,%111,%112,%113,%114,%115,%116,%117,%118,%119}, %120, %121, p, 1, 1, 0, 1;\n}\n"
    : "+f"(d[0]), "+f"(d[1]), "+f"(d[2]), "+f"(d[3]), "+f"(d[4]), "+f"(d[5]), "+f"(d[6]), "+f"(d[7]), "+f"(d[8]), "+f"(d[9]),
      "+f"(d[10]), "+f"(d[11]), "+f"(d[12]), "+f"(d[13]), "+f"(d[14]), "+f"(d[15]), "+f"(d[16]), "+f"(d[17]), "+f"(d[18]), "+f"(d[19]),
      "+f"(d[20]), "+f"(d[21]), "+f"(d[22]), "+f"(d[23]), "+f"(d[24]), "+f"(d[25]), "+f"(d[26]), "+f"(d[27]), "+f"(d[28]), "+f"(d[29]),
      "+f"(d[30]), "+f"(d[31]), "+f"(d[32]), "+f"(d[33]), "+f"(d[34]), "+f"(d[35]), "+f"(d[36]), "+f"(d[37]), "+f"(d[38]), "+f"(d[39]),
      "+f"(d[40]), "+f"(d[41]), "+f"(d[42]), "+f"(d[43]), "+f"(d[44]), "+f"(d[45]), "+f"(d[46]), "+f"(d[47]), "+f"(d[48]), "+f"(d[49]),
      "+f"(d[50]), "+f"(d[51]), "+f"(d[52]), "+f"(d[53]), "+f"(d[54]), "+f"(d[55]), "+f"(d[56]), "+f"(d[57]), "+f"(d[58]), "+f"(d[59]),
      "+f"(d[60]), "+f"(d[61]), "+f"(d[62]), "+f"(d[63]), "+f"(d[64]), "+f"(d[65]), "+f"(d[66]), "+f"(d[67]), "+f"(d[68]), "+f"(d[69]),
      "+f"(d[70]), "+f"(d[71]), "+f"(d[72]), "+f"(d[73]), "+f"(d[74]), "+f"(d[75]), "+f"(d[76]), "+f"(d[77]), "+f"(d[78]), "+f"(d[79]),
      "+f"(d[80]), "+f"(d[81]), "+f"(d[82]), "+f"(d[83]), "+f"(d[84]), "+f"(d[85]), "+f"(d[86]), "+f"(d[87]), "+f"(d[88]), "+f"(d[89]),
      "+f"(d[90]), "+f"(d[91]), "+f"(d[92]), "+f"(d[93]), "+f"(d[94]), "+f"(d[95]), "+f"(d[96]), "+f"(d[97]), "+f"(d[98]), "+f"(d[99]),
      "+f"(d[100]), "+f"(d[101]), "+f"(d[102]), "+f"(d[103]), "+f"(d[104]), "+f"(d[105]), "+f"(d[106]), "+f"(d[107]), "+f"(d[108]), "+f"(d[109]),
      "+f"(d[110]), "+f"(d[111]), "+f"(d[112]), "+f"(d[113]), "+f"(d[114]), "+f"(d[115]), "+f"(d[116]), "+f"(d[117]), "+f"(d[118]), "+f"(d[119])
    : "l"(da), "l"(db), "r"(scale_d));
}
__device__ __forceinline__ void wgmma_ss_n80_tb(float (&d)[40], uint64_t da, uint64_t db, int scale_d) {
  asm volatile("{\n.reg .pred p;\nsetp.ne.b32 p, %42, 0;\n"
    "wgmma.mma_async.sync.aligned.m64n80k16.f32.bf16.bf16 {%0,%1,%2,%3,%4,%5,%6,%7,%8,%9,%10,%11,%12,%13,%14,%15,%16,%17,%18,%19,%20,%21,%22,%23,%24,%25,%26,%27,%28,%29,%30,%31,%32,%33,%34,%35,%36,%37,%38,%39}, %40, %41, p, 1, 1, 0, 1;\n}\n"
    : "+f"(d[0]), "+f"(d[1]), "+f"(d[2]), "+f"(d[3]), "+f"(d[4]), "+f"(d[5]), "+f"(d[6]), "+f"(d[7]), "+f"(d[8]), "+f"(d[9]),
      "+f"(d[10]), "+f"(d[11]), "+f"(d[12]), "+f"(d[13]), "+f"(d[14]), "+f"(d[15]), "+f"(d[16]), "+f"(d[17]), "+f"(d[18]), "+f"(d[19]),
      "+f"(d[20]), "+f"(d[21]), "+f"(d[22]), "+f"(d[23]), "+f"(d[24]), "+f"(d[25]), "+f"(d[26]), "+f"(d[27]), "+f"(d[28]), "+f"(d[29]),
      "+f"(d[30]), "+f"(d[31]), "+f"(d[32]), "+f"(d[33]), "+f"(d[34]), "+f"(d[35]), "+f"(d[36]), "+f"(d[37]), "+f"(d[38]), "+f"(d[39])
    : "l"(da), "l"(db), "r"(scale_d));
}

__device__ __forceinline__ void wg_fence() { asm volatile("wgmma.fence.sync.aligned;" ::: "memory"); }
__device__ __forceinline__ void wg_commit() { asm volatile("wgmma.commit_group.sync.aligned;" ::: "memory"); }
template <int N> __device__ __forceinline__ void wg_wait() { asm volatile("wgmma.wait_group.sync.aligned %0;" ::"n"(N) : "memory"); }
__host__ __device__ constexpr uint64_t mkdesc(uint32_t addr, uint32_t lbo, uint32_t sbo, uint32_t sw) {
    return (uint64_t)((addr & 0x3FFFF) >> 4) | ((uint64_t)(lbo >> 4) << 16) | ((uint64_t)(sbo >> 4) << 32) | ((uint64_t)sw << 62);
}
__device__ __forceinline__ uint64_t mk64(uint32_t lo, uint32_t hi) {
    uint64_t d;
    asm volatile("mov.b64 %0, {%1, %2};" : "=l"(d) : "r"(lo), "r"(hi));
    return d;
}
template <int N> __device__ __forceinline__ void pin(float (&r)[N]) {
#pragma unroll
    for (int i = 0; i < N; i++) asm volatile("" : "+f"(r[i])::"memory");
}
template <int N> __device__ __forceinline__ void pin(uint32_t (&r)[N]) {
#pragma unroll
    for (int i = 0; i < N; i++) asm volatile("" : "+r"(r[i])::"memory");
}
__device__ __forceinline__ uint32_t pack2(float lo, float hi) {
    uint32_t r;
    asm("cvt.rn.bf16x2.f32 %0, %1, %2;" : "=r"(r) : "f"(hi), "f"(lo));
    return r;
}
__device__ __forceinline__ uint32_t mul2(uint32_t a, uint32_t b) {
    uint32_t r;
    asm("mul.rn.bf16x2 %0, %1, %2;" : "=r"(r) : "r"(a), "r"(b));
    return r;
}
__device__ __forceinline__ uint32_t selp(uint32_t a, uint32_t b, bool c) {
    uint32_t r;
    asm("{\n.reg .pred p;\nsetp.ne.u32 p, %3, 0;\nselp.b32 %0, %1, %2, p;\n}" : "=r"(r) : "r"(a), "r"(b), "r"((uint32_t)c));
    return r;
}
__device__ __forceinline__ float maxnan(float a, float b) {
    float r;
    asm("max.NaN.f32 %0, %1, %2;" : "=f"(r) : "f"(fabsf(a)), "f"(fabsf(b)));
    return r;
}
__device__ __forceinline__ void mbar_wait(uint32_t bar, uint32_t par) {
    asm volatile("{\n.reg .pred p;\n.reg .u32 c;\n"
                 "mbarrier.try_wait.parity.shared::cta.b64 p, [%0], %1;\n"
                 "@p bra DONE;\n"
                 "mov.u32 c, 0;\n"
                 "LOOP:\n"
                 "mbarrier.try_wait.parity.shared::cta.b64 p, [%0], %1;\n"
                 "@p bra DONE;\n"
                 "add.u32 c, c, 1;\n"
                 "setp.lt.u32 p, c, 1048576;\n"
                 "@p bra LOOP;\n"
                 "trap;\n"
                 "DONE:\n}" ::"r"(bar), "r"(par) : "memory");
}
__device__ __forceinline__ void mbar_arrive(uint32_t bar) {
    asm volatile("mbarrier.arrive.shared::cta.b64 _, [%0];" ::"r"(bar) : "memory");
}
__device__ __forceinline__ unsigned ld_relaxed(const unsigned* c) {
    unsigned v;
    asm volatile("ld.relaxed.gpu.global.u32 %0, [%1];" : "=r"(v) : "l"(c) : "memory");
    return v;
}
__device__ __forceinline__ void wait_cnt(const unsigned* c, unsigned target) {
    for (uint32_t tries = 0; (int)(ld_relaxed(c) - target) < 0; tries++)
        if (tries > (1u << 22)) asm volatile("trap;");
    asm volatile("fence.acquire.gpu;" ::: "memory");
}
__device__ __forceinline__ void proxy_fence() { asm volatile("fence.proxy.async.global;" ::: "memory"); }
__device__ __forceinline__ void red_release(unsigned* c) {
    proxy_fence();
    asm volatile("red.release.gpu.global.add.u32 [%0], 1;" ::"l"(c) : "memory");
}
__device__ __forceinline__ void warp_arrive(uint32_t bar, int lane) {
    __syncwarp();
    if (lane == 0) mbar_arrive(bar);
}
#define ELECT "{\n.reg .pred p;\nelect.sync _|p, 0xffffffff;\n@p "
__device__ __forceinline__ void mbar_expect(uint32_t bar, uint32_t bytes) {
    asm volatile(ELECT "mbarrier.arrive.expect_tx.shared::cta.b64 _, [%0], %1;\n}" ::"r"(bar), "r"(bytes) : "memory");
}
__device__ __forceinline__ void tma2d(uint32_t dst, const CUtensorMap* tm, int c0, int c1, uint32_t bar) {
    asm volatile(ELECT "cp.async.bulk.tensor.2d.shared::cluster.global.mbarrier::complete_tx::bytes [%0], [%1, {%3, %4}], [%2];\n}"
                 ::"r"(dst), "l"(tm), "r"(bar), "r"(c0), "r"(c1) : "memory");
}
__device__ __forceinline__ void tma2d_mc(uint32_t dst, const CUtensorMap* tm, int c0, int c1, uint32_t bar) {
    asm volatile(ELECT "cp.async.bulk.tensor.2d.shared::cluster.global.mbarrier::complete_tx::bytes.multicast::cluster [%0], [%1, {%3, %4}], [%2], %5;\n}"
                 ::"r"(dst), "l"(tm), "r"(bar), "r"(c0), "r"(c1), "h"((uint16_t)3) : "memory");
}
__device__ __forceinline__ void prefetch2d(const CUtensorMap* tm, int c0, int c1) {
    asm volatile(ELECT "cp.async.bulk.prefetch.tensor.2d.L2.global [%0, {%1, %2}];\n}" ::"l"(tm), "r"(c0), "r"(c1) : "memory");
}
__device__ __forceinline__ void bulk(uint32_t dst, const void* src, uint32_t bytes, uint32_t bar) {
    asm volatile(ELECT "cp.async.bulk.shared::cluster.global.mbarrier::complete_tx::bytes [%0], [%1], %2, [%3];\n}"
                 ::"r"(dst), "l"(src), "r"(bytes), "r"(bar) : "memory");
}
__device__ __forceinline__ void bulk_mc(uint32_t dst, const void* src, uint32_t bytes, uint32_t bar) {
    asm volatile(ELECT "cp.async.bulk.shared::cluster.global.mbarrier::complete_tx::bytes.multicast::cluster [%0], [%1], %2, [%3], %4;\n}"
                 ::"r"(dst), "l"(src), "r"(bytes), "r"(bar), "h"((uint16_t)3) : "memory");
}
__device__ __forceinline__ void bulk_st(void* dst, uint32_t src, uint32_t bytes) {
    asm volatile("cp.async.bulk.global.shared::cta.bulk_group [%0], [%1], %2;" ::"l"(dst), "r"(src), "r"(bytes) : "memory");
}
__device__ __forceinline__ void bulk_st_wait() { asm volatile("cp.async.bulk.commit_group;\ncp.async.bulk.wait_group 0;" ::: "memory"); }
__device__ __forceinline__ void stsm4(uint32_t a, uint32_t r0, uint32_t r1, uint32_t r2, uint32_t r3) {
    asm volatile("stmatrix.sync.aligned.m8n8.x4.shared.b16 [%0], {%1, %2, %3, %4};" ::"r"(a), "r"(r0), "r"(r1), "r"(r2), "r"(r3) : "memory");
}
__device__ __forceinline__ void cluster_arrive() { asm volatile("barrier.cluster.arrive.relaxed.aligned;" ::: "memory"); }
__device__ __forceinline__ void cluster_wait() { asm volatile("barrier.cluster.wait.aligned;" ::: "memory"); }
__device__ __forceinline__ void bsync(int id) { asm volatile("bar.sync %0, 256;" ::"r"(id) : "memory"); }
__device__ __forceinline__ void barrive(int id) { asm volatile("bar.arrive %0, 256;" ::"r"(id) : "memory"); }
__device__ __forceinline__ uint32_t lds32(uint32_t a) {
    uint32_t v;
    asm volatile("ld.shared.u32 %0, [%1];" : "=r"(v) : "r"(a) : "memory");
    return v;
}
__device__ __forceinline__ uint4 lds128(uint32_t a) {
    uint4 v;
    asm volatile("ld.shared.v4.u32 {%0, %1, %2, %3}, [%4];" : "=r"(v.x), "=r"(v.y), "=r"(v.z), "=r"(v.w) : "r"(a) : "memory");
    return v;
}
__device__ __forceinline__ float bf_lo(uint32_t w) { return __uint_as_float(w << 16); }
__device__ __forceinline__ float bf_hi(uint32_t w) { return __uint_as_float(w & 0xffff0000u); }

__device__ __forceinline__ uint32_t exp_mufu(float a, float b) {
    float x, y;
    asm("ex2.approx.ftz.f32 %0, %1;" : "=f"(x) : "f"(a));
    asm("ex2.approx.ftz.f32 %0, %1;" : "=f"(y) : "f"(b));
    return pack2(x, y);
}
__device__ __forceinline__ uint32_t exp_pack(float a, float b) {
    uint32_t w;
    asm("prmt.b32 %0, %1, %2, 0x6521;" : "=r"(w) : "r"(__float_as_uint(a)), "r"(__float_as_uint(b)));
    return w;
}
__device__ __forceinline__ uint32_t exp_poly(uint32_t w, uint32_t c1, uint32_t c2) {
    uint32_t z, e, r, g;
    asm("lop3.b32 %0, %1, 0x007f007f, %2, 0xEA;" : "=r"(z) : "r"(w), "r"(c1));
    asm("lop3.b32 %0, %1, 0xff80ff80, %2, 0x6A;" : "=r"(e) : "r"(w), "r"(c2));
    asm("fma.rn.bf16x2 %0, %1, %1, %2;" : "=r"(g) : "r"(z), "r"(0x40034003));
    asm("fma.rn.relu.bf16x2 %0, %1, %2, %3;" : "=r"(r) : "r"(e), "r"(g), "r"(0));
    return r;
}
__device__ __forceinline__ void exp_tile(float (&s)[64], uint32_t (&p)[32]) {
    pin(s);
#pragma unroll
    for (int i = 0; i < 32; i++)
        p[i] = (PMASK >> (i >> 1)) & 1 ? exp_poly(exp_pack(s[2 * i], s[2 * i + 1]), 0x3f803f80u, 0x80008000u) : exp_mufu(s[2 * i], s[2 * i + 1]);
    pin(p);
}
__device__ __forceinline__ void store_out(__nv_bfloat16* dst, const float (&d)[40], int tt) {
#pragma unroll
    for (int r = 0; r < 2; r++) {
        const float* a = &d[2 * r];
#pragma unroll
        for (int qq = 0; qq < 2; qq++) {
            uint4 v;
            v.x = pack2(a[16 * qq + 0], a[16 * qq + 1]);
            v.y = pack2(a[16 * qq + 4], a[16 * qq + 5]);
            v.z = pack2(a[16 * qq + 8], a[16 * qq + 9]);
            v.w = pack2(a[16 * qq + 12], a[16 * qq + 13]);
            *reinterpret_cast<uint4*>(dst + r * 8 * 1280 + 32 * qq + 8 * tt) = v;
        }
        uint2 u;
        u.x = pack2(a[32], a[33]);
        u.y = pack2(a[36], a[37]);
        *reinterpret_cast<uint2*>(dst + r * 8 * 1280 + 64 + 4 * tt) = u;
    }
}

__device__ __forceinline__ int mpos(int m) { return (m >> 1) + 8 * (m & 1); }

__device__ __forceinline__ void load24(float (&v)[24], const __nv_bfloat16* base, int ps, float sc, bool odd) {
#pragma unroll
    for (int pl = 0; pl < 3; pl++) {
        uint4 u = __ldcg(reinterpret_cast<const uint4*>(base + pl * ps));
        if (pl == 2) { if (odd) { u.x = 0; u.y = 0; } else { u.z = 0; u.w = 0; } }
        v[8 * pl + 0] = bf_lo(u.x) * sc; v[8 * pl + 1] = bf_hi(u.x) * sc;
        v[8 * pl + 2] = bf_lo(u.y) * sc; v[8 * pl + 3] = bf_hi(u.y) * sc;
        v[8 * pl + 4] = bf_lo(u.z) * sc; v[8 * pl + 5] = bf_hi(u.z) * sc;
        v[8 * pl + 6] = bf_lo(u.w) * sc; v[8 * pl + 7] = bf_hi(u.w) * sc;
    }
}
__device__ __forceinline__ void attention_fallback(int h, int qm, int row0, int lane) {
    const bool odd = h & 1;
#pragma unroll 1
    for (int r = 0; r < 16; r++) {
        float q[24], acc[24];
        load24(q, g_qkv + (size_t)(h * 16 + mpos(qm)) * 3072 + (row0 + r) * 8, 1024, 0x1p62f, odd);
#pragma unroll
        for (int i = 0; i < 24; i++) acc[i] = 0.f;
        float m = -INFINITY, l = 0.f;
#pragma unroll 1
        for (int j = lane; j < 2048; j += 32) {
            float kv[24];
            const int kr = j & 127;
            load24(kv, g_qkv + (size_t)((32 + h) * 16 + (j >> 7)) * 3072 + kr * 8, 1024, ((PMASK >> (kr >> 3)) & 1) ? 0x1p72f : 0x1p-62f, odd);
            float s = 0.f;
#pragma unroll
            for (int i = 0; i < 24; i++) s = fmaf(q[i], kv[i], s);
            const float mn = fmaxf(m, s);
            const float c = exp2f(m - mn), p = exp2f(s - mn);
            m = mn;
            l = l * c + p;
            load24(kv, g_qkv + (size_t)((64 + h) * 16 + (((j >> 7) + 1) & 15)) * 3072 + kr * 8 + (kr >> 3) * 128, 64, 1.f, odd);
#pragma unroll
            for (int i = 0; i < 24; i++) acc[i] = fmaf(p, kv[i], acc[i] * c);
        }
        float M = m;
#pragma unroll
        for (int o = 16; o > 0; o >>= 1) M = fmaxf(M, __shfl_xor_sync(0xffffffffu, M, o));
        const float c = exp2f(m - M);
        l *= c;
#pragma unroll
        for (int o = 16; o > 0; o >>= 1) l += __shfl_xor_sync(0xffffffffu, l, o);
        float val = 0.f;
#pragma unroll
        for (int i = 0; i < 24; i++) {
            float a = acc[i] * c;
#pragma unroll
            for (int o = 16; o > 0; o >>= 1) a += __shfl_xor_sync(0xffffffffu, a, o);
            if (lane == i) val = a;
        }
        const bool valid = lane < 16 || (odd ? (lane >= 20 && lane < 24) : lane < 20);
        if (valid) {
            const int pl = lane >> 3;
            const int chunk = 5 * (h >> 1) + (pl == 2 ? 2 : pl + (odd ? 3 : 0));
            g_o[(size_t)((2 * qm + (row0 >> 6)) * 80 + chunk) * 512 + ((row0 & 63) + r) * 8 + (lane & 7)] = __float2bfloat16(val / l);
        }
    }
}

template <int V> struct IntC { static constexpr int value = V; };
struct Maps { CUtensorMap x, wqkv, bx, wr, wi, cr, ci; uint64_t dk, dv, da, db; };

__global__ void __cluster_dims__(2, 1, 1) __launch_bounds__(384, 1)
fused_kernel(const __grid_constant__ Maps tm, const uint32_t* __restrict__ wo, __nv_bfloat16* __restrict__ out) {
    extern __shared__ __align__(1024) uint8_t smem[];
    const uint32_t sb = (uint32_t)__cvta_generic_to_shared(smem);
    const uint32_t bars = sb + BAR_OFF;
    const int tid = threadIdx.x, lane = tid & 31;
    const int wg = __shfl_sync(0xffffffffu, tid >> 7, 0);
    const int b = blockIdx.x, pair = b >> 1, rank = b & 1;
    const int nt = pair & 7, mt = 2 * (pair >> 3) + rank;
    const int head = pair >> 1, quarter = 2 * (pair & 1) + rank;
    const int gi = pair >> 2, gj = 2 * (pair & 3) + rank;
    const bool odd = head & 1;
    const int oa = (gi & 12) + ((gi >> 1) & 1), ob = (gi & 12) + 3 - ((gi >> 1) & 1);

    const int wid = __shfl_sync(0xffffffffu, tid >> 5, 0);
    auto init = [&](int off, int n, int cnt) {
        for (int i = 0; i < n; i++) asm volatile("mbarrier.init.shared::cta.b64 [%0], %1;" ::"r"(bars + off + 8 * i), "r"(cnt));
    };
    if (wid == 9) {
        if (lane == 0) {
            init(B_FULL + 8, 3, 1); init(B_EMPTY, 4, 16); init(B_PUB, 1, 8); init(B_PUB + 8, 1, 10); init(B_KVOK, 1, 1); init(B_ABOK, 3, 1); init(B_KV2, 5, 1);
            init(B_QRDY, 4, 2); init(B_OST, 4, 8); init(B_ST, 6, 8); init(B_GO, 4, 1);
            asm volatile("fence.mbarrier_init.release.cluster;" ::: "memory");
            if ((sb & 0xFFFFFF) != SB) asm volatile("trap;");
        }
        if (lane < 15) asm volatile("st.shared.u32 [%0], %1;" ::"r"(bars + B_KN + 4 * lane), "r"(0) : "memory");
    }
    if (wid == 8) {
        if (lane == 0) {
            init(B_FULL, 1, 1);
            asm volatile("fence.mbarrier_init.release.cluster;" ::: "memory");
        }
        __syncwarp();
        cluster_arrive();
        mbar_expect(bars + B_FULL, 49152);
        tma2d(sb, &tm.x, 0, 128 * mt, bars + B_FULL);
#pragma unroll
        for (int c = 0; c < 4; c++) tma2d(sb + 16384 + c * 8192, &tm.wqkv, 240 * nt + 64 * c, 0, bars + B_FULL);
    } else {
        __syncwarp();
        cluster_arrive();
    }
    __syncwarp();
    cluster_wait();

    if (wg == 2) {
        asm volatile("setmaxnreg.dec.sync.aligned.u32 40;");
        const int pw = wid & 3;
        auto shift_q = [&](int i0, int i1) {
            mbar_wait(bars + B_QLD, 0);
            __syncwarp();
            const float kmax2 = 0.9235f * __uint_as_float(__reduce_max_sync(0xffffffffu, lds32(sb + O_KN + (lane & 7) * 4)));
#pragma unroll 1
            for (int i = i0; i < i1; i++) {
                const uint32_t a = sb + (i >> 2) * SLOT + O_Q + ((i & 3) * 32 + lane) * 16;
                const uint4 u0 = lds128(a), u1 = lds128(a + 2048), u2 = lds128(a + 4096);
                const uint32_t w[10] = {u0.x, u0.y, u0.z, u0.w, u1.x, u1.y, u1.z, u1.w, odd ? u2.z : u2.x, odd ? u2.w : u2.y};
                float n2 = 0.f;
#pragma unroll
                for (int j = 0; j < 10; j++) {
                    const float x = bf_lo(w[j]) * 0x1p62f, y = bf_hi(w[j]) * 0x1p62f;
                    n2 = fmaf(x, x, fmaf(y, y, n2));
                }
                float B;
                asm("sqrt.approx.f32 %0, %1;" : "=f"(B) : "f"(n2 * kmax2));
                const float m = fmaxf(0.5f * B, B - 126.f);
                const uint32_t bq = __ballot_sync(0xffffffffu, !(B + m <= 630.f));
                if (lane == 0) asm volatile("st.shared.u32 [%0], %1;" ::"r"(bars + B_BADQ + 4 * i), "r"(bq) : "memory");
                asm volatile("st.shared.u16 [%0], %1;" ::"r"(a + 4096 + (odd ? 0 : 8)), "h"((uint16_t)pack2(-m * 0x1p-62f, 0.f)) : "memory");
                if (i & 1) warp_arrive(bars + B_QRDY + 8 * (i >> 2), lane);
            }
        };
        const uint32_t lateq = (mt & 3) ? (nt < 2 ? 0x3b : nt == 2 ? 0x0b : 0) : 0;
        auto put = [&](int pp, int last) {
            if (last >= 0) {
                mbar_wait(bars + B_ST + 8 * last, 0);
                asm volatile("fence.proxy.async.shared::cta;" ::: "memory");
            }
            const int slot = 12 * nt + 2 * pp;
            __nv_bfloat16* d = g_qkv + (size_t)(slot * 16 + ((mpos(mt) + (slot >> 6)) & 15)) * 3072;
            bulk_st(d, sb + stage_off(pp), 6144);
            if (pp == 1) {
                for (int i = 0; i < 3; i++) bulk_st(d + 16 * 3072 + i * 1024, sb + (i + 1) * SLOT + O_KN, 2048);
            } else {
                bulk_st(d + 16 * 3072, sb + stage_off(pp) + 6144, 6144);
            }
        };
        if (pw == 0) {
            auto acquire = [&](uint32_t n, uint32_t bytes) {
                mbar_wait(bars + B_EMPTY + 8 * (n & 3), ((n >> 2) & 1) ^ 1);
                __syncwarp();
                mbar_expect(bars + B_FULL + 8 * (n & 3), bytes);
            };
#pragma unroll 1
            for (uint32_t k = 1; k < 10; k++) {
                const uint32_t sl = sb + (k & 3) * SLOT, fb = bars + B_FULL + 8 * (k & 3);
                acquire(k, 49152);
                tma2d(sl, &tm.x, 64 * k, 128 * mt, fb);
                tma2d_mc(sl + 16384 + rank * 16384, &tm.wqkv, 240 * nt + 128 * rank, 64 * k, fb);
                tma2d_mc(sl + 16384 + rank * 16384 + 8192, &tm.wqkv, 240 * nt + 128 * rank + 64, 64 * k, fb);
            }
            const unsigned ep = g_epoch[b] + 1;
#pragma unroll 1
            for (uint32_t k = 0; k < 10; k++) {
                const uint32_t sl = sb + ((k + 2) & 3) * SLOT, fb = bars + B_FULL + 8 * ((k + 2) & 3);
                if (k == 5 && rank == 0) mbar_wait(bars + B_GO, 0);
                acquire(10 + k, 16384 + 20480);
                tma2d(sl, &tm.bx, 64 * k, 128 * mt, fb);
                tma2d_mc(sl + 16384 + rank * 10240, rank ? &tm.wi : &tm.wr, 64 * k, 80 * nt, fb);
            }
            mbar_wait(bars + B_KVOK, 0);
            proxy_fence();
            const __nv_bfloat16* kvsrc = g_qkv + (size_t)((32 + 32 * rank + head) * 16) * 3072;
            const uint32_t kvdst = sb + O_K + rank * 6144;
#pragma unroll 1
            for (uint32_t it = 0; it < 4; it++) {
                acquire(20 + it, (it ? 12288 : 6144));
                if (it >= rank) bulk_mc(kvdst + it * SLOT, kvsrc + it * 3072, 6144, bars + B_FULL + 8 * it);
            }
            mbar_expect(bars + B_KV2, 4 * 12288);
#pragma unroll 1
            for (uint32_t it = 0; it < 4; it++) bulk_mc(kvdst - O_K + it * SLOT, kvsrc + (4 + it) * 3072, 6144, bars + B_KV2);
            if (lane == 0) { mbar_arrive(bars + B_GAOK); }
            mbar_wait(bars + B_ABOK, 0);
            proxy_fence();
            __syncwarp();
#pragma unroll 1
            for (uint32_t i4 = LAG / 4; i4 < 16; i4++) {
                const __nv_bfloat16* src = kvsrc + (i4 & 3) * 4 * 3072;
#pragma unroll
                for (uint32_t j = 0; j < 4; j++) {
                    mbar_wait(bars + B_EMPTY + 8 * j, ~i4 & 1);
                    mbar_expect(bars + B_FULL + 8 * j, 12288 + 16384 + 10240);
                    bulk_mc(kvdst + j * SLOT, src + j * 3072, 6144, bars + B_FULL + 8 * j);
                }
            }
#pragma unroll 1
            for (uint32_t it = 64; it < 64 + LAG; it++) {
                const uint32_t sl = (it & 3) * SLOT, fb = bars + B_FULL + 8 * (it & 3);
                acquire(16 + it, (it == 64 ? 6144 : 0) + 16384 + 10240);
                if (it == 64 && rank) bulk_mc(kvdst + sl, kvsrc, 6144, fb);
                if (it == 65) mbar_expect(bars + B_W1, 3 * 12800);
                if (it >= 65 && it < 68) bulk(sb + sl + O_W1, g_wo + (gj * 8 + 4 + (it & 3)) * 6400, 12800, bars + B_W1);
            }
            constexpr uint32_t N0 = 16 + 64 + LAG;
            static_assert(N0 % 4 == 0 && LAG == 8, "");
#pragma unroll 1
            for (uint32_t k = 0; k < 8; k++) {
                if ((k & 3) == 0) {
                    mbar_wait(bars + B_OOK + 2 * k, 0);
                    proxy_fence();
                }
                acquire(N0 + k, 20480);
                bulk_mc(sb + (k & 3) * SLOT + rank * 10240, g_o + (size_t)((2 * (k < 4 ? oa : ob) + (gi & 1)) * 8 + 2 * (k & 3) + rank) * 5120, 10240, bars + B_FULL + 8 * (k & 3));
            }
            if (lane == 0) g_epoch[b] = ep;
        } else if (pw == 1) {
            const unsigned ep = g_epoch[b] + 1;
            mbar_wait(bars + B_FULL + 8, 0);
            mbar_wait(bars + B_FULL + 8, 1);
            __syncwarp();
            prefetch2d(&tm.bx, 64 * nt, 128 * mt);
            if (nt < 2) prefetch2d(&tm.bx, 64 * (8 + nt), 128 * mt);
            if (mt < 10) { prefetch2d(&tm.wr, 64 * mt, 80 * nt); prefetch2d(&tm.wi, 64 * mt, 80 * nt); }
            auto go1 = [&]() { asm volatile("{\n.reg .u32 a;\nmapa.shared::cluster.u32 a, %0, 1;\nmbarrier.arrive.shared::cluster.b64 _, [a];\n}" ::"r"(bars + B_GO) : "memory"); };
            if (rank == 0) {
                mbar_expect(bars + B_KNX, 48);
                if (lane == 0) {
#pragma unroll 1
                    for (int pp = 0; pp < 6; pp++) {
                        if (!((lateq >> pp) & 1)) put(pp, pp);
                        if (pp == 5) go1();
                    }
                    bulk_st_wait();
                    mbar_arrive(bars + B_GO);
                }
                __syncwarp();
                mbar_wait(bars + B_PUB, 0);
                mbar_wait(bars + B_KNX, 0);
                if (lane < 12 && ((12 * nt + lane) >> 5) == 1)
                    g_kn[(12 * nt + lane - 32) * 8 + (mt >> 1)] = max(lds32(bars + B_KN + 4 * lane), lds32(bars + B_KN2 + 4 * lane));
                __syncwarp();
                if (lane == 0) {
                    red_release(g_cnt + 32 * nt);
                }
            } else if (lane == 0) {
                put(2, 2);
                asm volatile("cp.async.bulk.commit_group;" ::: "memory");
                mbar_wait(bars + B_GO, 0);
#pragma unroll 1
                for (int pp = 0; pp < 6; pp++) if (pp != 2 && !((lateq >> pp) & 1)) put(pp, pp);
                asm volatile("cp.async.bulk.wait_group.read 0;" ::: "memory");
            }
            __syncwarp();
            if (lane < 3) wait_cnt(g_cnt + 32 * ((32 * lane + head) / 12), ep * 8);
            warp_arrive(bars + B_KVOK, lane);
            proxy_fence();
            __syncwarp();
            mbar_expect(bars + B_QLD, 6144 + 32);
            bulk(sb + O_KN, g_kn + head * 8, 32, bars + B_QLD);
            bulk(sb + O_Q, g_qkv + (size_t)(head * 16 + mpos(quarter * 4)) * 3072, 6144, bars + B_QLD);
            if (lane == 0) {
                bulk_st_wait();
                mbar_wait(bars + B_PUB + 8, 0);
                red_release(g_cnt + 32 * (8 + nt));
            }
            __syncwarp();
            if (lane < 4) wait_cnt(g_cnt + 32 * (8 + (lane < 3 ? (32 * lane + head) / 12 : gj)), ep * 16);
            warp_arrive(bars + B_ABOK, lane);
            if (lane == 0) {
                if (lateq) mbar_wait(bars + B_LQD, 0);
                wait_cnt(g_cnt + 32 * (32 + head / 12), ep * 12);
            }
            __syncwarp();
            proxy_fence();
            __syncwarp();
            mbar_expect(bars + B_QLD + 8, 3 * 6144);
#pragma unroll 1
            for (int p = 1; p < 4; p++)
                bulk(sb + p * SLOT + O_Q, g_qkv + (size_t)(head * 16 + mpos(quarter * 4 + p)) * 3072, 6144, bars + B_QLD + 8);
            mbar_wait(bars + B_QLD + 8, 0);
            shift_q(4, 16);
#pragma unroll 1
            for (int pass = 0; pass < 4; pass++) {
                mbar_wait(bars + B_OST + 8 * pass, 0);
                if (lane == 0) {
                    if (!((lds32(bars + B_FAIL) >> (8 * pass)) & 1)) red_release(g_cnt + 32 * (16 + quarter * 4 + pass));
                }
                __syncwarp();
                if (pass == 2) {
                    mbar_expect(bars + B_W0, 5 * 12800);
#pragma unroll 1
                    for (int k = 0; k < 5; k++) bulk(sb + (k < 4 ? k * SLOT + O_W0 : X_OFF), g_wo + (gj * 8 + k) * 6400, 12800, bars + B_W0);
                }
                if (lane < 2 && pass == 2 + lane) {
                    wait_cnt(g_cnt + 32 * (16 + (lane ? ob : oa)), ep * 32);
                    mbar_arrive(bars + B_OOK + 8 * lane);
                }
                __syncwarp();
            }
        } else {
            const int hw = pw - 2;
#pragma unroll 1
            for (int i = hw * 32 + lane; i < 400; i += 64) {
                const int c = i / 40, kr = i - 40 * c, k = 40 * mt + kr;
                const uint32_t* src = wo + k * 320 + 40 * nt + (c < 8 ? 16 * (c >> 2) + (c & 3) : 32 + (c & 1));
                const int st = c < 8 ? 4 : 2;
                uint4 v;
                v.x = __ldg(src); v.y = __ldg(src + st); v.z = __ldg(src + 2 * st); v.w = __ldg(src + 3 * st);
                *reinterpret_cast<uint4*>(g_wo + (nt * 8 + (mt >> 1)) * 6400 + c * 640 + (40 * (mt & 1) + kr) * 8) = v;
            }
            warp_arrive(bars + B_PUB + 8, lane);
            if (rank == 1 && hw == 0) {
                mbar_wait(bars + B_PUB, 0);
                asm volatile("{\n.reg .u32 a, m;\n.reg .pred p;\nsetp.lt.u32 p, %3, 12;\nmapa.shared::cluster.u32 a, %0, 0;\nmapa.shared::cluster.u32 m, %1, 0;\n"
                             "@p st.async.shared::cluster.mbarrier::complete_tx::bytes.u32 [a], %2, [m];\n}"
                             ::"r"(bars + B_KN2 + 4 * (lane & 15)), "r"(bars + B_KNX), "r"(lds32(bars + B_KN + 4 * (lane & 15))), "r"(lane) : "memory");
            }
            if (hw == 0) {
                if (lateq && lane == 0) {
                    mbar_wait(bars + B_GAOK, 0);
#pragma unroll 1
                    for (int pp = 0; pp < 6; pp++) if ((lateq >> pp) & 1) put(pp, pp ? -1 : 5);
                    bulk_st_wait();
                    mbar_arrive(bars + B_LQD);
                    red_release(g_cnt + 32 * (32 + nt));
                }
                __syncwarp();
                mbar_wait(bars + B_GAOK, 0);
                mbar_wait(bars + B_ABOK, 0);
                proxy_fence();
                const __nv_bfloat16* src = g_ab + (size_t)gj * 64 * 5120;
#pragma unroll 1
                for (uint32_t i4 = LAG / 4; i4 < 16 + LAG / 4; i4++, src += 4 * 5120) {
#pragma unroll
                    for (uint32_t j = 0; j < 4; j++) {
                        mbar_wait(bars + B_EMPTY + 8 * j, ~i4 & 1);
                        bulk(sb + j * SLOT + O_GB, src + j * 5120, 10240, bars + B_FULL + 8 * j);
                    }
                }
            } else {
                const int row = 128 * gi + 64 * rank;
                prefetch2d(&tm.cr, 64 * (pair & 3), row);
                mbar_wait(bars + B_GAOK, 0);
#pragma unroll 1
                for (uint32_t g4 = 0; g4 < 16; g4++) {
                    const CUtensorMap* cm = g4 < 8 ? &tm.cr : &tm.ci;
#pragma unroll
                    for (uint32_t j = 0; j < 4; j++) {
                        mbar_wait(bars + B_EMPTY + 8 * j, ~g4 & 1);
                        tma2d_mc(sb + rank * 8192 + j * SLOT, cm, 256 * (g4 & 7) + 64 * j, row, bars + B_FULL + 8 * j);
                    }
                }
            }
        }
        __syncwarp();
        asm volatile("barrier.cluster.arrive.relaxed.aligned;\nbarrier.cluster.wait.aligned;" ::: "memory");
    } else {
        asm volatile("setmaxnreg.inc.sync.aligned.u32 232;");
        const int warp = (tid >> 5) & 3, g8 = lane >> 2, tt = lane & 3;
        uint32_t rel_addr;
        asm("mapa.shared::cluster.u32 %0, %1, %2;" : "=r"(rel_addr) : "r"(bars + B_EMPTY), "r"(lane & 1));
        auto release = [&](uint32_t n) {
            if (lane < 2) asm volatile("mbarrier.arrive.shared::cluster.b64 _, [%0];" ::"r"(rel_addr + 8 * (n & 3)) : "memory");
        };
        auto wait_full = [&](uint32_t n) { mbar_wait(bars + B_FULL + 8 * (n & 3), (n >> 2) & 1); __syncwarp(); };
        const int row0 = wg * 64 + warp * 16;
        const uint64_t da_sw = tm.da + wg * 512;

        const int blk = row0 >> 3;
        const bool pl0 = (PMASK >> blk) & 1, pl1 = (PMASK >> (blk + 1)) & 1, to = tt & 1;
        uint32_t w2[40];
        {
            float acc1[120];
#pragma unroll
            for (int i = 0; i < 120; i++) acc1[i] = 0.f;
            pin(acc1);
            constexpr uint64_t db1 = mkdesc(SB + 16384, 8192, 1024, 1);
#pragma unroll 1
            for (uint32_t k = 0; k < 10; k++) {
                wait_full(k);
                const uint64_t so = (k & 3) * (SLOT >> 4);
                wg_fence();
#pragma unroll
                for (int j = 0; j < 4; j++) wgmma_ss_n240_tb(acc1, da_sw + so + 2 * j, db1 + so + 128 * j, 1);
                wg_commit();
                wg_wait<1>();
                if (k > 0) release(k - 1);
            }
            wg_wait<0>();
            pin(acc1);
            release(9);
            float acc[80];
            constexpr uint64_t db0 = mkdesc(SB + 16384, 16, 1024, 1);
            uint32_t sc0, sc1, ax0, ax1, ar1, ar2;
            const uint32_t hi = lane >> 4, rr = row0 + (lane & 15);
            auto emit = [&](int pp, bool setup) {
                const float* a = &acc1[20 * pp];
                if (setup) {
                    const int ty = (12 * nt + 2 * pp) >> 5;
                    const uint32_t kaxp = to ? 0x172A1BB3u : 0x1FBE1B80u, kaxm = to ? 0u : 0x5E80u;
                    const uint32_t sc = ty == 0 ? 0x1FAE1FAEu : 0x3F803F80u, ax = ty == 0 ? (to ? 0x20802080u : 0x20800000u) : (to ? 0u : 0x3F80u);
                    sc0 = selp(pl0 ? 0x1B731B73u : 0x5E735E73u, sc, ty == 1);
                    sc1 = selp(pl1 ? 0x1B731B73u : 0x5E735E73u, sc, ty == 1);
                    ax0 = selp(pl0 ? kaxp : kaxm, ax, ty == 1);
                    ax1 = selp(pl1 ? kaxp : kaxm, ax, ty == 1);
                    const uint32_t ro = rr * 16 + (ty == 2 ? (rr >> 3) * 256 : 0), ps = ty == 2 ? 128 : 2048;
                    ar1 = ro + hi * ps;
                    ar2 = ro + 2 * ps;
                }
                const uint32_t off = sb + stage_off(pp);
                auto split = [&](uint32_t x) { return sb + SLOT + O_KN + (x >> 11) * SLOT + (x & 2047); };
                stsm4(ar1 + off, mul2(pack2(a[0], a[1]), sc0), mul2(pack2(a[2], a[3]), sc1), mul2(pack2(a[4], a[5]), sc0), mul2(pack2(a[6], a[7]), sc1));
                stsm4(pp == 1 ? split(ar1) : ar1 + off + 6144, mul2(pack2(a[12], a[13]), sc0), mul2(pack2(a[14], a[15]), sc1),
                      mul2(pack2(a[16], a[17]), sc0), mul2(pack2(a[18], a[19]), sc1));
                const uint32_t w4 = mul2(pack2(a[8], a[9]), sc0), w5 = mul2(pack2(a[10], a[11]), sc1);
                stsm4(pp == 1 && hi ? split(ar2) : ar2 + off + hi * 6144, tt < 2 ? w4 : ax0, tt < 2 ? w5 : ax1, tt < 2 ? ax0 : w4, tt < 2 ? ax1 : w5);
                warp_arrive(bars + B_ST + 8 * pp, lane);
            };
            auto knorm = [&](int p2) {
                if (((12 * nt + 4 * p2) >> 5) == 1) {
                    float kk[2];
#pragma unroll
                    for (int h = 0; h < 2; h++) {
                        const float* a = &acc1[40 * p2 + 20 * h];
                        const float e0 = a[0] * a[0] + a[1] * a[1] + a[4] * a[4] + a[5] * a[5];
                        const float e1 = a[2] * a[2] + a[3] * a[3] + a[6] * a[6] + a[7] * a[7];
                        const float o0 = a[12] * a[12] + a[13] * a[13] + a[16] * a[16] + a[17] * a[17];
                        const float o1 = a[14] * a[14] + a[15] * a[15] + a[18] * a[18] + a[19] * a[19];
                        const float k0 = fmaf(a[8], a[8], fmaf(a[9], a[9], tt < 2 ? e0 : o0)) + __shfl_xor_sync(0xffffffffu, tt < 2 ? o0 : e0, 2);
                        const float k1 = fmaf(a[10], a[10], fmaf(a[11], a[11], tt < 2 ? e1 : o1)) + __shfl_xor_sync(0xffffffffu, tt < 2 ? o1 : e1, 2);
                        kk[h] = (to ? k1 : k0) + __shfl_xor_sync(0xffffffffu, to ? k0 : k1, 1);
                    }
                    uint32_t v = max(__float_as_uint(to ? kk[1] : kk[0]), __float_as_uint(__shfl_xor_sync(0xffffffffu, to ? kk[0] : kk[1], 1)));
                    v = max(v, __shfl_xor_sync(0xffffffffu, v, 16));
                    if (lane < 16) asm volatile("red.shared.max.u32 [%0], %1;" ::"r"(bars + B_KN + 16 * p2 + 8 * to + 2 * (tt & 2)), "r"(v) : "memory");
                }
            };
#pragma unroll
            for (int k = 0; k < 10; k++) {
                wait_full(10 + k);
                constexpr uint64_t SO = SLOT >> 4;
                wg_fence();
#pragma unroll
                for (int j = 0; j < 4; j++) {
                    if (k == 0 && j == 0) wgmma_ss_n160_init(acc, da_sw + ((10 + k) & 3) * SO + 2 * j, db0 + ((10 + k) & 3) * SO + 2 * j);
                    else wgmma_ss_n160(acc, da_sw + ((10 + k) & 3) * SO + 2 * j, db0 + ((10 + k) & 3) * SO + 2 * j, 1);
                }
                wg_commit();
                if (k == 0) { emit(0, true); emit(1, false); bsync(5); emit(2, true); }
                if (k == 1) { emit(3, false); emit(4, true); emit(5, false); }
                if (k == 2) { knorm(0); knorm(1); }
                if (k == 3) { knorm(2); warp_arrive(bars + B_PUB, lane); }
                wg_wait<1>();
                if (k > 0) release(10 + k - 1);
            }
            wg_wait<0>();
            pin(acc);
            release(19);
#pragma unroll
            for (int i = 0; i < 20; i++) {
                w2[i] = pack2(acc[2 * i], acc[2 * i + 1]);
                w2[20 + i] = pack2(-acc[40 + 2 * i], -acc[40 + 2 * i + 1]);
            }
            pin(w2);
        }
        uint32_t fail = 0;
        float d[40];
        __nv_bfloat16* outp = out + (size_t)(128 * gi + row0 + g8) * 1280 + 80 * gj;
        {
            float s[64], o[12];
            uint32_t p0[32], p1[32], q[6];
#pragma unroll
            for (int i = 0; i < 12; i++) o[i] = 0.f;
#pragma unroll
            for (int i = 0; i < 32; i++) p1[i] = 0u;
            pin(o); pin(p1);
            const uint64_t dv0 = tm.dv, db0 = tm.db;
            const uint32_t hh = tm.dk >> 32, ha = tm.da >> 32, la = (uint32_t)da_sw;
            auto store_ab = [&](int hb) {
                uint32_t* dst = reinterpret_cast<uint32_t*>(g_ab + (size_t)(nt * 64 + hb * 32 + 2 * mt + wg) * 5120) + warp * 640 + g8 * 4;
#pragma unroll
                for (int r = 0; r < 2; r++) {
                    const uint32_t* a = &w2[20 * hb + r];
#pragma unroll
                    for (int qq = 0; qq < 2; qq++)
                        *reinterpret_cast<uint4*>(dst + (4 * qq + tt) * 32 + r * 320) = make_uint4(a[8 * qq], a[8 * qq + 2], a[8 * qq + 4], a[8 * qq + 6]);
                    dst[(8 + (tt & 1)) * 32 + r * 320 + (tt >> 1)] = a[16];
                    dst[(8 + (tt & 1)) * 32 + r * 320 + 2 + (tt >> 1)] = a[18];
                }
            };
            auto load_q = [&](uint32_t pass, uint32_t bar) {
                mbar_wait(bars + bar, 0);
                __syncwarp();
                const uint32_t a = sb + pass * SLOT + O_Q + (row0 + g8) * 16 + tt * 4;
                q[0] = lds32(a); q[1] = lds32(a + 128); q[2] = lds32(a + 2048); q[3] = lds32(a + 2048 + 128);
                q[4] = lds32(a + 4096); q[5] = lds32(a + 4096 + 128);
            };
            auto dump_o = [&](uint32_t pass) {
                const int src = (lane & 28) | (odd ? 0 : 2);
                const bool dat = (tt < 2) != odd;
                const float l0 = __shfl_sync(0xffffffffu, o[8], src), l1 = __shfl_sync(0xffffffffu, o[10], src);
                uint32_t bq;
                asm volatile("ld.shared.u16 %0, [%1];" : "=r"(bq) : "r"(bars + B_BADQ + 16 * pass + (row0 >> 3)) : "memory");
                float i0, i1;
                asm("rcp.approx.ftz.f32 %0, %1;" : "=f"(i0) : "f"(l0));
                asm("rcp.approx.ftz.f32 %0, %1;" : "=f"(i1) : "f"(l1));
                uint32_t* dst = reinterpret_cast<uint32_t*>(g_o + (size_t)((quarter * 8 + 2 * pass + wg) * 80 + 5 * (head >> 1)) * 512) + (warp * 16 + g8) * 4 + tt;
                uint32_t* dm = dst + (odd ? 3 * 256 : 0);
                dm[0] = pack2(o[0] * i0, o[1] * i0);   dm[32] = pack2(o[2] * i1, o[3] * i1);
                dm[256] = pack2(o[4] * i0, o[5] * i0); dm[288] = pack2(o[6] * i1, o[7] * i1);
                asm volatile("{\n.reg .pred p;\nsetp.ne.u32 p, %3, 0;\n@p st.global.u32 [%0+2048], %1;\n@p st.global.u32 [%0+2176], %2;\n}"
                             ::"l"(dst), "r"(pack2(o[8] * i0, o[9] * i0)), "r"(pack2(o[10] * i1, o[11] * i1)), "r"((uint32_t)dat) : "memory");
                const float x0 = maxnan(maxnan(maxnan(o[0], o[1]), maxnan(o[4], o[5])), dat ? maxnan(o[8], o[9]) : 0.f);
                const float x1 = maxnan(maxnan(maxnan(o[2], o[3]), maxnan(o[6], o[7])), dat ? maxnan(o[10], o[11]) : 0.f);
                uint32_t t0 = __ballot_sync(0xffffffffu, l0 < 1.f && x0 < 0x1p-95f), t1 = __ballot_sync(0xffffffffu, l1 < 1.f && x1 < 0x1p-95f);
                t0 &= t0 >> 1; t1 &= t1 >> 1;
                const bool ok = l0 >= 0x1p-95f && l0 <= 0x1p126f && l1 >= 0x1p-95f && l1 <= 0x1p126f && x0 <= 0x1.fffffep127f && x1 <= 0x1.fffffep127f;
                const uint32_t bad = ((((t0 & (t0 >> 2)) | (t1 & (t1 >> 2))) & 0x11111111u) | bq | __ballot_sync(0xffffffffu, !ok));
                asm volatile("{\n.reg .pred p;\nsetp.ne.u32 p, %2, 0;\n@p st.shared.u8 [%1], 1;\n@p or.b32 %0, %0, %3;\n}"
                             : "+r"(fail) : "r"(bars + B_FAIL + pass), "r"(bad), "r"(1u << pass) : "memory");
                warp_arrive(bars + B_OST + 8 * pass, lane);
            };
            const int bar_m = __shfl_sync(0xffffffffu, 1 + (tid >> 7), 0), bar_o = __shfl_sync(0xffffffffu, 2 - (tid >> 7), 0);
            auto tile = [&](uint32_t i4, uint32_t (&pi)[32], uint32_t (&po)[32], auto jc, auto mode) {
                constexpr int J = decltype(jc)::value, MODE = decltype(mode)::value;
                constexpr uint64_t so = J * (SLOT >> 4);
                const uint32_t par = MODE == 2 ? (i4 & 1) ^ (J == 3) : MODE == 0 && J < 3;
                constexpr int NEXT = MODE == 2 || (MODE == 0) == (J < 3) ? B_FULL + 8 * ((J + 1) & 3) : B_KV2, OK = MODE == 1 ? 0 : O_K;
                constexpr uint32_t dk = (uint32_t)mkdesc(SB + OK, 2048, 128, 0) + so, dv = (uint32_t)mkdesc(SB + OK + 6144, 384, 128, 0) + so,
                                   db = (uint32_t)mkdesc(SB + O_GB, 1280, 128, 0) + so;
                bsync(bar_m);
                wg_fence();
                wgmma_rs_n128_init(s, q[0], q[1], q[2], q[3], mk64(dk, hh));
                wgmma_rs_n128(s, 0, 0, q[4], q[5], mk64(dk + 128, hh), 1);
                if (MODE != 2) wg_commit();
#pragma unroll
                for (int k = 0; k < 8; k++) {
                    wgmma_rs_n24_tb(o, pi[4 * k], pi[4 * k + 1], pi[4 * k + 2], pi[4 * k + 3], mk64(dv + 48 * k, hh), J == 1 && k == 0 ? (i4 & 3) != 0 : 1);
                }
                if constexpr (MODE == 2) {
                    wg_commit();
#pragma unroll
                    for (int j = 0; j < 4; j++) wgmma_ss_n80_tb(d, mk64(la + (uint32_t)so + 2 * j, ha), mk64(db + 160 * j, hh), 1);
                }
                wg_commit();
                barrive(bar_o);
                if constexpr (MODE == 0 && J == 0) {
                    store_ab(1);
                    warp_arrive(bars + B_PUB + 8, lane);
                }
                wg_wait<1>();
                if constexpr (MODE == 2 && J == 0) {
                    pin(o);
                    if ((i4 & 3) == 0) {
                        dump_o((i4 >> 2) - 1);
                        exp_tile(s, po);
                    } else {
                        exp_tile(s, po);
                        asm volatile("// plain" ::: "memory");
                    }
                } else {
                    exp_tile(s, po);
                }
                mbar_wait(bars + NEXT, par);
                wg_wait<0>();
                pin(o); pin(pi);
                if constexpr (MODE == 2) pin(d);
                if constexpr (MODE != 0) release(J);
                if constexpr (MODE == 2 && J == 3) { if ((i4 & 3) == 3 && i4 < 15) load_q((i4 >> 2) + 1, B_QRDY + 8 + 8 * (i4 >> 2)); pin(q); }
            };
            auto group = [&](uint32_t i4, auto mode) {
                tile(i4, p1, p0, IntC<0>(), mode);
                tile(i4, p0, p1, IntC<1>(), mode);
                tile(i4, p1, p0, IntC<2>(), mode);
                tile(i4, p0, p1, IntC<3>(), mode);
            };
            if (wg == 1) barrive(1);
            store_ab(0);
            load_q(0, B_QLD);
            {
                const float kmax2 = 0.9235f * __uint_as_float(__reduce_max_sync(0xffffffffu, lds32(sb + O_KN + (lane & 7) * 4)));
                bool bad = false;
#pragma unroll
                for (int r = 0; r < 2; r++) {
                    float n2 = 0.f;
#pragma unroll
                    for (int j = 0; j < 3; j++) {
                        const uint32_t w = j == 2 && (tt < 2) == odd ? 0u : q[2 * j + r];
                        const float x = bf_lo(w) * 0x1p62f, y = bf_hi(w) * 0x1p62f;
                        n2 = fmaf(x, x, fmaf(y, y, n2));
                    }
                    n2 += __shfl_xor_sync(0xffffffffu, n2, 1);
                    n2 += __shfl_xor_sync(0xffffffffu, n2, 2);
                    float B;
                    asm("sqrt.approx.f32 %0, %1;" : "=f"(B) : "f"(n2 * kmax2));
                    const float m = fmaxf(0.5f * B, B - 126.f);
                    bad |= !(B + m <= 630.f);
                    if (tt == (odd ? 0 : 2)) q[4 + r] |= pack2(-m * 0x1p-62f, 0.f);
                }
                asm volatile("st.shared.u16 [%0], %1;" ::"r"(bars + B_BADQ + (row0 >> 3)), "h"((uint16_t)__any_sync(0xffffffffu, bad)) : "memory");
                __syncwarp();
            }
            wait_full(20);
            pin(q);
            group(0, IntC<0>());
            group(1, IntC<1>());
#pragma unroll
            for (int i = 0; i < 40; i++) d[i] = 0.f;
            pin(d);
#pragma unroll 1
            for (uint32_t i4 = LAG / 4; i4 < 16; i4++) group(i4, IntC<2>());
            if (wg == 0) bsync(1);
            {
                wg_fence();
#pragma unroll
                for (int k = 0; k < 8; k++) wgmma_rs_n24_tb(o, p1[4 * k], p1[4 * k + 1], p1[4 * k + 2], p1[4 * k + 3], dv0 + 48 * k, 1);
                wg_commit();
                auto gstep = [&](uint32_t it) {
                    const uint64_t so = (it & 3) * (SLOT >> 4);
#pragma unroll
                    for (int j = 0; j < 4; j++) wgmma_ss_n80_tb(d, da_sw + so + 2 * j, db0 + so + 160 * j, 1);
                    wg_commit();
                };
                gstep(64);
                wg_wait<0>();
                pin(o); pin(p1);
                release(0);
                dump_o(3);
#pragma unroll 1
                for (uint32_t it = 65; it < 64 + LAG; it++) {
                    wait_full(16 + it);
                    wg_fence();
                    gstep(it);
                    wg_wait<0>();
                    release(it);
                }
                pin(d);
            }
            if (wg) store_out(outp + 640, d, tt);
        }
        mbar_wait(bars + B_OST + 24, 0);
        __syncwarp();
        const uint32_t anyfail = lds32(bars + B_FAIL);
        if (anyfail) {
#pragma unroll 1
            for (int pass = 0; pass < 4; pass++) {
                if ((anyfail >> (8 * pass)) & 1) {
                    if ((fail >> pass) & 1) attention_fallback(head, quarter * 4 + pass, row0, lane);
                    bsync(5);
                    if (tid == 0) red_release(g_cnt + 32 * (16 + quarter * 4 + pass));
                }
            }
        }
        __syncwarp();
        {
            float acc[40];
#pragma unroll
            for (int i = 0; i < 40; i++) acc[i] = 0.f;
            pin(acc);
            constexpr uint64_t da0 = mkdesc(SB, 1024, 128, 0), db0 = mkdesc(SB, 128, 1280, 0);
            constexpr uint32_t N0 = 16 + 64 + LAG;
            mbar_wait(bars + B_W0, 0);
            mbar_wait(bars + B_W1, 0);
#pragma unroll 1
            for (uint32_t k = 0; k < 4 * wg; k++) { wait_full(N0 + k); release(k); }
#pragma unroll
            for (uint32_t k = 0; k < 4; k++) {
                wait_full(N0 + k + 4 * wg);
                wg_fence();
#pragma unroll
                for (int j = 0; j < 10; j++) {
                    const int u = 2 * k + j / 5;
                    wgmma_ss_n80_tb(acc, da0 + k * (SLOT >> 4) + 128 * j, db0 + ((u == 4 ? X_OFF : (u & 3) * SLOT + (u < 4 ? O_W0 : O_W1)) >> 4) + 16 * (j % 5), 1);
                }
                wg_commit();
                if (k == 3) wg_wait<0>(); else wg_wait<1>();
                if (wg == 0 && k > 0) release(k - 1);
                if (wg == 0 && k == 3) release(3);
            }
            wg_wait<0>();
            pin(acc);
            cluster_arrive();
            if (wg == 0) store_out(outp + 640, d, tt);
            store_out(out + (size_t)(128 * (wg ? ob : oa) + 64 * (gi & 1) + warp * 16 + g8) * 1280 + 80 * gj, acc, tt);
            cluster_wait();
        }
    }
}

typedef CUresult (*EncodeFn)(CUtensorMap*, CUtensorMapDataType, cuuint32_t, void*, const cuuint64_t*, const cuuint64_t*,
                             const cuuint32_t*, const cuuint32_t*, CUtensorMapInterleave, CUtensorMapSwizzle,
                             CUtensorMapL2promotion, CUtensorMapFloatOOBfill);

void make2d(EncodeFn enc, CUtensorMap* m, void* p, uint64_t cols, uint64_t rows, uint32_t bc, uint32_t br, bool p256) {
    cuuint64_t dims[2] = {cols, rows}, strides[1] = {cols * 2};
    cuuint32_t box[2] = {bc, br}, es[2] = {1, 1};
    enc(m, CU_TENSOR_MAP_DATA_TYPE_BFLOAT16, 2, p, dims, strides, box, es, CU_TENSOR_MAP_INTERLEAVE_NONE,
        CU_TENSOR_MAP_SWIZZLE_128B, p256 ? CU_TENSOR_MAP_L2_PROMOTION_L2_256B : CU_TENSOR_MAP_L2_PROMOTION_L2_128B, CU_TENSOR_MAP_FLOAT_OOB_FILL_NONE);
}

}

extern "C" void kernel_launch(void* const* d_in, const int* in_sizes, int n_in, void* d_out, int out_size) {
    (void)in_sizes; (void)n_in; (void)out_size;
    void* fn = nullptr;
    cudaDriverEntryPointQueryResult qr;
    cudaGetDriverEntryPoint("cuTensorMapEncodeTiled", &fn, cudaEnableDefault, &qr);
    EncodeFn enc = (EncodeFn)fn;
    Maps m;
    make2d(enc, &m.x, d_in[0], 640, 2048, 64, 128, false);
    make2d(enc, &m.wqkv, d_in[1], 1920, 640, 64, 64, false);
    make2d(enc, &m.bx, d_in[3], 640, 2048, 64, 128, false);
    make2d(enc, &m.cr, d_in[4], 2048, 2048, 64, 64, true);
    make2d(enc, &m.ci, d_in[5], 2048, 2048, 64, 64, true);
    make2d(enc, &m.wr, d_in[6], 640, 640, 64, 80, false);
    make2d(enc, &m.wi, d_in[7], 640, 640, 64, 80, false);
    m.dk = mkdesc(SB + O_K, 2048, 128, 0); m.dv = mkdesc(SB + O_V, 384, 128, 0);
    m.da = mkdesc(SB, 16, 1024, 1); m.db = mkdesc(SB + O_GB, 1280, 128, 0);
    cudaFuncSetAttribute(fused_kernel, cudaFuncAttributeMaxDynamicSharedMemorySize, SMEM_BYTES);
    fused_kernel<<<128, 384, SMEM_BYTES>>>(m, (const uint32_t*)d_in[2], (__nv_bfloat16*)d_out);
}
```
